```python
import torch

def _softmax(x, axis=-1):
    return torch.softmax(x, dim=axis)
def _gelu(x):
    return torch.nn.functional.gelu(x, approximate="tanh")
def _silu(x):
    return torch.nn.functional.silu(x)
def _sigmoid(x):
    return torch.sigmoid(x)
def _layernorm(x, axis=-1, eps=1e-5):
    m = x.mean(dim=axis, keepdim=True)
    v = x.var(dim=axis, keepdim=True, unbiased=False)
    return (x - m) / torch.sqrt(v + eps)
def _scatter_add(tgt, idx, src, axis=0):
    return tgt.clone().index_add_(axis, idx, src)
def _segment_sum(src, seg, n):
    out = torch.zeros((n,) + src.shape[1:], dtype=src.dtype)
    return out.index_add_(0, seg, src)
def _pad(x, pw):
    flat = tuple(v for pair in reversed(pw) for v in pair)
    return torch.nn.functional.pad(x, flat)

kernel_name = 'standalone__deep_cross_pnn__recsys'

def setup_inputs():

    _w = (lambda a: (lambda t: t.to(torch.bfloat16) if t.is_floating_point() else t)(torch.as_tensor(a)))
    B, F, D, V = 4096, 26, 128, min(100000, 100000)
    H = 4 * D
    return {
        "idx": _w((lambda lo, hi, *s: torch.randint(lo, hi, s))(0, V, B, F).to(torch.int64)),
        "table": _w((lambda *s: torch.randn(*s, dtype=torch.bfloat16) * 1.6)(V, D) * (D ** -0.5)),
        "w_p": _w((lambda *s: torch.randn(*s, dtype=torch.bfloat16) * 0.05)(F * F) * ((F * F) ** -0.5)),
        "w1": _w((lambda *s: torch.randn(*s, dtype=torch.bfloat16) * 1.6)(F * D, H) * ((F * D) ** -0.5)),
        "b1": _w((lambda *s: torch.randn(*s, dtype=torch.bfloat16) * 12.8)(H) * 0.01),
        "w2": _w((lambda *s: torch.randn(*s, dtype=torch.bfloat16) * 0.05)(H) * (H ** -0.5)),
        "b2": _w((lambda *s: torch.randn(*s, dtype=torch.bfloat16) * 12.8)(1) * 0.01),
    }

def reference(idx, table, w_p, w1, b1, w2, b2):
    emb = table[idx]
    B = emb.shape[0]; F = emb.shape[1]; D = emb.shape[2]
    ip = torch.einsum('bid,bjd->bij', emb, emb)
    ip = ip.reshape(B, F * F)
    logit_p = ip @ w_p
    z = emb.reshape(B, F * D)
    h = _gelu(z @ w1 + b1)
    logit_d = h @ w2 + b2
    return logit_p + logit_d
```

```cpp
#include <cuda_runtime.h>
#include <cuda_bf16.h>
#include <cuda.h>
#include <stdint.h>

namespace {

constexpr int kB = 4096, kF = 26, kD = 128, kH = 512;
constexpr int NST = 4;
constexpr uint32_t STAGE = 32768;
constexpr uint32_t OFF_RECV = NST * STAGE;
constexpr uint32_t OFF_IDX  = OFF_RECV + 32768;
constexpr uint32_t OFF_WTS  = OFF_IDX + 128 * kF * 4;
constexpr uint32_t OFF_W2   = OFF_WTS + 2560;
constexpr uint32_t OFF_PART = OFF_W2 + 512;
constexpr uint32_t OFF_BAR  = OFF_PART + 256;
constexpr uint32_t SMEM_USED = OFF_BAR + 17 * 8;
constexpr uint32_t SMEM_BYTES = SMEM_USED + 1024;
constexpr uint32_t BAR_FULL = OFF_BAR, BAR_EMPTY = OFF_BAR + 32, BAR_IDX = OFF_BAR + 64, BAR_RECV = OFF_BAR + 72;

__device__ unsigned long long g_slots[32 * 4 * 4 * 32];
#define STAMP(i)
#define GSTAMP(i)

__device__ __forceinline__ void wgmma_n128_lo(float (&d)[128], uint32_t a0, uint32_t a1, uint32_t a2, uint32_t a3, uint64_t db) {
  asm volatile("wgmma.mma_async.sync.aligned.m64n128k16.f32.bf16.bf16 "
    "{%0, %1, %2, %3, %4, %5, %6, %7, %8, %9, %10, %11, %12, %13, %14, %15, %16, %17, %18, %19, %20, %21, %22, %23, %24, %25, %26, %27, %28, %29, %30, %31, %32, %33, %34, %35, %36, %37, %38, %39, %40, %41, %42, %43, %44, %45, %46, %47, %48, %49, %50, %51, %52, %53, %54, %55, %56, %57, %58, %59, %60, %61, %62, %63}, "
    "{%64, %65, %66, %67}, %68, 1, 1, 1, 1;\n"
    : "+f"(d[0]), "+f"(d[1]), "+f"(d[2]), "+f"(d[3]), "+f"(d[4]), "+f"(d[5]), "+f"(d[6]), "+f"(d[7]), "+f"(d[8]), "+f"(d[9]), "+f"(d[10]), "+f"(d[11]), "+f"(d[12]), "+f"(d[13]), "+f"(d[14]), "+f"(d[15]), "+f"(d[16]), "+f"(d[17]), "+f"(d[18]), "+f"(d[19]), "+f"(d[20]), "+f"(d[21]), "+f"(d[22]), "+f"(d[23]), "+f"(d[24]), "+f"(d[25]), "+f"(d[26]), "+f"(d[27]), "+f"(d[28]), "+f"(d[29]), "+f"(d[30]), "+f"(d[31]), "+f"(d[32]), "+f"(d[33]), "+f"(d[34]), "+f"(d[35]), "+f"(d[36]), "+f"(d[37]), "+f"(d[38]), "+f"(d[39]), "+f"(d[40]), "+f"(d[41]), "+f"(d[42]), "+f"(d[43]), "+f"(d[44]), "+f"(d[45]), "+f"(d[46]), "+f"(d[47]), "+f"(d[48]), "+f"(d[49]), "+f"(d[50]), "+f"(d[51]), "+f"(d[52]), "+f"(d[53]), "+f"(d[54]), "+f"(d[55]), "+f"(d[56]), "+f"(d[57]), "+f"(d[58]), "+f"(d[59]), "+f"(d[60]), "+f"(d[61]), "+f"(d[62]), "+f"(d[63])
    : "r"(a0), "r"(a1), "r"(a2), "r"(a3), "l"(db));
}
__device__ __forceinline__ void wgmma_n128_hi(float (&d)[128], uint32_t a0, uint32_t a1, uint32_t a2, uint32_t a3, uint64_t db) {
  asm volatile("wgmma.mma_async.sync.aligned.m64n128k16.f32.bf16.bf16 "
    "{%0, %1, %2, %3, %4, %5, %6, %7, %8, %9, %10, %11, %12, %13, %14, %15, %16, %17, %18, %19, %20, %21, %22, %23, %24, %25, %26, %27, %28, %29, %30, %31, %32, %33, %34, %35, %36, %37, %38, %39, %40, %41, %42, %43, %44, %45, %46, %47, %48, %49, %50, %51, %52, %53, %54, %55, %56, %57, %58, %59, %60, %61, %62, %63}, "
    "{%64, %65, %66, %67}, %68, 1, 1, 1, 1;\n"
    : "+f"(d[64]), "+f"(d[65]), "+f"(d[66]), "+f"(d[67]), "+f"(d[68]), "+f"(d[69]), "+f"(d[70]), "+f"(d[71]), "+f"(d[72]), "+f"(d[73]), "+f"(d[74]), "+f"(d[75]), "+f"(d[76]), "+f"(d[77]), "+f"(d[78]), "+f"(d[79]), "+f"(d[80]), "+f"(d[81]), "+f"(d[82]), "+f"(d[83]), "+f"(d[84]), "+f"(d[85]), "+f"(d[86]), "+f"(d[87]), "+f"(d[88]), "+f"(d[89]), "+f"(d[90]), "+f"(d[91]), "+f"(d[92]), "+f"(d[93]), "+f"(d[94]), "+f"(d[95]), "+f"(d[96]), "+f"(d[97]), "+f"(d[98]), "+f"(d[99]), "+f"(d[100]), "+f"(d[101]), "+f"(d[102]), "+f"(d[103]), "+f"(d[104]), "+f"(d[105]), "+f"(d[106]), "+f"(d[107]), "+f"(d[108]), "+f"(d[109]), "+f"(d[110]), "+f"(d[111]), "+f"(d[112]), "+f"(d[113]), "+f"(d[114]), "+f"(d[115]), "+f"(d[116]), "+f"(d[117]), "+f"(d[118]), "+f"(d[119]), "+f"(d[120]), "+f"(d[121]), "+f"(d[122]), "+f"(d[123]), "+f"(d[124]), "+f"(d[125]), "+f"(d[126]), "+f"(d[127])
    : "r"(a0), "r"(a1), "r"(a2), "r"(a3), "l"(db));
}

__device__ __forceinline__ uint32_t smem_u32(const void* p) { return (uint32_t)__cvta_generic_to_shared(p); }
__device__ __forceinline__ void mbar_init(uint32_t bar, uint32_t cnt) { asm volatile("mbarrier.init.shared::cta.b64 [%0], %1;" :: "r"(bar), "r"(cnt)); }
__device__ __forceinline__ void mbar_expect_tx(uint32_t bar, uint32_t bytes) { asm volatile("mbarrier.arrive.expect_tx.shared::cta.b64 _, [%0], %1;" :: "r"(bar), "r"(bytes) : "memory"); }
__device__ __forceinline__ void mbar_arrive(uint32_t bar) { asm volatile("mbarrier.arrive.shared::cta.b64 _, [%0];" :: "r"(bar) : "memory"); }
__device__ __forceinline__ void mbar_wait(uint32_t bar, uint32_t parity) {
  asm volatile("{\n.reg .pred p;\n.reg .u32 c;\nmov.u32 c, 0;\n"
    "LAB_WAIT:\nmbarrier.try_wait.parity.shared::cta.b64 p, [%0], %1;\n@p bra.uni LAB_DONE;\n"
    "add.u32 c, c, 1;\nsetp.lt.u32 p, c, 4000000;\n@p bra.uni LAB_WAIT;\ntrap;\nLAB_DONE:\n}" :: "r"(bar), "r"(parity) : "memory");
}
__device__ __forceinline__ uint64_t make_desc(uint32_t addr) {
  return (uint64_t)((addr & 0x3FFFF) >> 4) | ((uint64_t)(8192 >> 4) << 16) | ((uint64_t)(1024 >> 4) << 32) | (1ull << 62);
}
__device__ __forceinline__ uint4 ldg128(const void* p) {
  uint4 v;
  asm volatile("ld.global.nc.L1::no_allocate.v4.u32 {%0,%1,%2,%3}, [%4];" : "=r"(v.x), "=r"(v.y), "=r"(v.z), "=r"(v.w) : "l"(p));
  return v;
}
__device__ __forceinline__ uint32_t lds32(uint32_t a) { uint32_t v; asm volatile("ld.shared.u32 %0, [%1];" : "=r"(v) : "r"(a)); return v; }
__device__ __forceinline__ void tma_w1(uint32_t dst, const CUtensorMap* tm, uint32_t bar, int x, int kb) {
  asm volatile("cp.async.bulk.tensor.5d.shared::cluster.global.mbarrier::complete_tx::bytes [%0], [%1, {%3, %4, %4, %4, %5}], [%2];"
    :: "r"(dst), "l"(tm), "r"(bar), "r"(x), "r"(0), "r"(kb) : "memory");
}
__device__ __forceinline__ float bf_lo(uint32_t v) { return __uint_as_float(v << 16); }
__device__ __forceinline__ float bf_hi(uint32_t v) { return __uint_as_float(v & 0xffff0000u); }
__device__ __forceinline__ uint32_t pack_bf16(float lo, float hi) { uint32_t r; asm("cvt.rn.bf16x2.f32 %0, %1, %2;" : "=r"(r) : "f"(hi), "f"(lo)); return r; }
__device__ __forceinline__ void mma16816(float (&d)[4], uint32_t a0, uint32_t a1, uint32_t a2, uint32_t a3, uint32_t b0, uint32_t b1) {
  asm volatile("mma.sync.aligned.m16n8k16.row.col.f32.bf16.bf16.f32 {%0,%1,%2,%3}, {%4,%5,%6,%7}, {%8,%9}, {%0,%1,%2,%3};"
    : "+f"(d[0]), "+f"(d[1]), "+f"(d[2]), "+f"(d[3]) : "r"(a0), "r"(a1), "r"(a2), "r"(a3), "r"(b0), "r"(b1));
}

__device__ __forceinline__ uint32_t rd_tid() { uint32_t v; asm volatile("mov.u32 %0, %tid.x;" : "=r"(v)); return v; }
__device__ __forceinline__ uint32_t rd_cta() { uint32_t v; asm volatile("mov.u32 %0, %ctaid.x;" : "=r"(v)); return v; }
template <int LO, int HI> __device__ __forceinline__ void fence_acc(float (&d)[128]) {
  #pragma unroll
  for (int i = LO; i < HI; i++) asm volatile("" : "+f"(d[i]) :: "memory");
}
__device__ __forceinline__ bool elect_one() {
  uint32_t p; asm volatile("{\n.reg .pred P;\nelect.sync _|P, 0xffffffff;\nselp.u32 %0, 1, 0, P;\n}" : "=r"(p)); return p != 0;
}
struct Half { uint4 x, y; };
struct Quad { uint4 a, b, c, e; };

__global__ void __cluster_dims__(2, 1, 1) __launch_bounds__(384, 1)
pnn_mlp_kernel(const __grid_constant__ CUtensorMap tmW, const int* __restrict__ idx, const char* __restrict__ table,
               const __nv_bfloat16* __restrict__ w_p, const __nv_bfloat16* __restrict__ b1, const __nv_bfloat16* __restrict__ w2,
               const __nv_bfloat16* __restrict__ b2, __nv_bfloat16* __restrict__ out, uint32_t zero) {
  extern __shared__ __align__(1024) uint8_t smem_raw[];
  const uint32_t sb = (smem_u32(smem_raw) + 1023) & ~1023u;
  const int tid = threadIdx.x;
  const int warp = __shfl_sync(0xffffffffu, tid >> 5, 0);
  const int kh = blockIdx.x & 1, pair = blockIdx.x >> 1, nh = pair & 1, mt = pair >> 1;
  const int f0 = kh * 13;

  if (tid == 0) {
    STAMP(0); GSTAMP(1);
    mbar_init(sb + BAR_IDX, 1);
    #pragma unroll
    for (int s = 0; s < NST; s++) { mbar_init(sb + BAR_FULL + s * 8, 4); mbar_init(sb + BAR_EMPTY + s * 8, 2); }
    #pragma unroll
    for (int w = 0; w < 8; w++) mbar_init(sb + BAR_RECV + w * 8, 1);
    asm volatile("fence.mbarrier_init.release.cluster;" ::: "memory");
    mbar_expect_tx(sb + BAR_IDX, 128 * kF * 4);
    asm volatile("cp.async.bulk.shared::cluster.global.mbarrier::complete_tx::bytes [%0], [%1], %2, [%3];"
      :: "r"(sb + OFF_IDX), "l"(idx + (size_t)mt * 128 * kF), "r"(128 * kF * 4), "r"(sb + BAR_IDX) : "memory");
  }

  if (warp >= 4) {
    const int t = tid - 128, c = (warp - 4) >> 2, w = warp & 3, lane = tid & 31, g = lane >> 2, q = lane & 3;
    const int r0 = c * 64 + w * 16 + g;
    const int* ip = idx + (size_t)(mt * 128 + r0) * kF + f0;
    const uint32_t i00 = __ldg(ip), i10 = __ldg(ip + 8 * kF), i01 = __ldg(ip + 1), i11 = __ldg(ip + 8 * kF + 1);
    uint32_t braw[16];
    {
      const uint32_t* bp = reinterpret_cast<const uint32_t*>(b1 + nh * 256 + kh * 128) + q;
      #pragma unroll
      for (int i = 0; i < 16; i++) braw[i] = __ldg(bp + i * 4);
    }
    __syncthreads();
    asm volatile("barrier.cluster.arrive.relaxed.aligned;" ::: "memory");
    asm volatile("setmaxnreg.inc.sync.aligned.u32 192;");
    const int xcol = nh * 256 + ((w ^ (kh ? 0 : 2)) << 6);
    if (c == 0 && elect_one()) {
      #pragma unroll
      for (int k = 0; k < NST; k++) {
        mbar_expect_tx(sb + BAR_FULL + k * 8, 8192);
        tma_w1(sb + k * STAGE + w * 8192, &tmW, sb + BAR_FULL + k * 8, xcol, f0 * 4 + k * 2);
      }
    }
    if (elect_one()) mbar_expect_tx(sb + BAR_RECV + (c * 4 + w) * 8, 4096);

    Half R[4];
    const char *p0, *p1;
    auto setptr = [&](uint32_t i0, uint32_t i1) {
      const uint32_t qq = rd_tid() & 3;
      p0 = table + (size_t)(i0 * 16u + qq) * 16u; p1 = table + (size_t)(i1 * 16u + qq) * 16u;
    };
    auto refill = [&](Half& h, int quarter) { h.x = ldg128(p0 + quarter * 64); h.y = ldg128(p1 + quarter * 64); };
    setptr(i00, i10);
    refill(R[0], 0); refill(R[1], 1); refill(R[2], 2); refill(R[3], 3);
    setptr(i01, i11);

    float acc[128];
    #pragma unroll
    for (int i = 0; i < 64; i++) acc[i] = 0.f;
    #pragma unroll
    for (int i = 0; i < 16; i++) {
      acc[64 + 4 * i + 0] = bf_lo(braw[i]); acc[64 + 4 * i + 1] = bf_hi(braw[i]);
      acc[64 + 4 * i + 2] = bf_lo(braw[i]); acc[64 + 4 * i + 3] = bf_hi(braw[i]);
    }
    fence_acc<0, 128>(acc);
    const uint32_t sidx0 = sb + OFF_IDX + (r0 * kF + f0) * 4;
    mbar_wait(sb + BAR_IDX, 0);
    if (t == 0) STAMP(2);

#define FRAG(h, u, v) uint32_t f0_ = h.x.u ^ zero, f1_ = h.y.u ^ zero, f2_ = h.x.v ^ zero, f3_ = h.y.v ^ zero
#define WG_FENCE()  asm volatile("wgmma.fence.sync.aligned;" ::: "memory")
#define WG_COMMIT() asm volatile("wgmma.commit_group.sync.aligned;" ::: "memory")
#define WG_WAIT(n)  asm volatile("wgmma.wait_group.sync.aligned " #n ";" ::: "memory")
#define XORZ(d, s)  asm volatile("xor.b32 %0, %1, %2;" : "=r"(d) : "r"(s), "r"(zero))
    auto mma256 = [&](uint32_t x0, uint32_t y0, uint32_t x1, uint32_t y1, uint32_t baddr) {
      uint32_t a0, a1, a2, a3;
      XORZ(a0, x0); XORZ(a1, y0); XORZ(a2, x1); XORZ(a3, y1);
      WG_FENCE(); wgmma_n128_lo(acc, a0, a1, a2, a3, make_desc(baddr)); wgmma_n128_hi(acc, a0, a1, a2, a3, make_desc(baddr + 2 * 8192)); WG_COMMIT();
    };
    uint32_t ni0 = 0, ni1 = 0;
    #pragma unroll 1
    for (int f = 0; f < 12; f++) {
      #pragma unroll
      for (int j = 0; j < 4; j++) {
        const int k = 2 * f + (j >> 1), s = k & 3;
        Half& h = R[j];
        if ((j & 1) == 0) mbar_wait(sb + BAR_FULL + s * 8, (k >> 2) & 1);
        if (j == 0 && f == 0 && t == 0) STAMP(3);
        const uint32_t bb = sb + s * STAGE + (j & 1) * 4096;
        mma256(h.x.x, h.y.x, h.x.y, h.y.y, bb);
        WG_WAIT(1);
        if ((j & 1) == 0 && k > 0 && w == 0) { if (elect_one()) mbar_arrive(sb + BAR_EMPTY + ((k - 1) & 3) * 8); }
        if (j == 2) {
          const int nf = min(f + 2, 12);
          ni0 = lds32(sidx0 + nf * 4); ni1 = lds32(sidx0 + nf * 4 + 8 * kF * 4);
        }
        mma256(h.x.z, h.y.z, h.x.w, h.y.w, bb + 2048);
        refill(h, j);
        if (j == 3) setptr(ni0, ni1);
        WG_WAIT(1);
        if ((j & 1) == 0 && c == 0 && k > 0 && k + 3 < 26) {
          const int sp = (k - 1) & 3;
          mbar_wait(sb + BAR_EMPTY + sp * 8, ((k - 1) >> 2) & 1);
          if (elect_one()) {
            mbar_expect_tx(sb + BAR_FULL + sp * 8, 8192);
            tma_w1(sb + sp * STAGE + w * 8192, &tmW, sb + BAR_FULL + sp * 8, xcol, f0 * 4 + (k + 3) * 2);
          }
        }
      }
    }
    WG_WAIT(0);
    {
    const uint32_t tid2 = rd_tid();
    const int t = tid2 - 128, lane = t & 31, g = lane >> 2, q = lane & 3;
    if (t == 0) STAMP(4);
    mbar_wait(sb + BAR_FULL + 0, 0);
    mbar_wait(sb + BAR_FULL + 8, 0);
    #pragma unroll
    for (int hh = 0; hh < 4; hh++) {
      const uint32_t bb = sb + (hh >> 1) * STAGE + (hh & 1) * 4096;
      Half& h = R[hh];
      { uint32_t a0, a1, a2, a3; XORZ(a0, h.x.x); XORZ(a1, h.y.x); XORZ(a2, h.x.y); XORZ(a3, h.y.y);
        WG_FENCE(); wgmma_n128_lo(acc, a0, a1, a2, a3, make_desc(bb)); WG_COMMIT(); WG_WAIT(1); }
      { uint32_t a0, a1, a2, a3; XORZ(a0, h.x.z); XORZ(a1, h.y.z); XORZ(a2, h.x.w); XORZ(a3, h.y.w);
        WG_FENCE(); wgmma_n128_lo(acc, a0, a1, a2, a3, make_desc(bb + 2048)); WG_COMMIT(); WG_WAIT(1); }
    }
    asm volatile("barrier.cluster.wait.aligned;" ::: "memory");
    uint32_t rdst, rbar;
    asm("mapa.shared::cluster.u32 %0, %1, %2;" : "=r"(rdst) : "r"(sb + OFF_RECV + t * 16), "r"(kh ^ 1));
    asm("mapa.shared::cluster.u32 %0, %1, %2;" : "=r"(rbar) : "r"(sb + BAR_RECV + (c * 4 + w) * 8), "r"(kh ^ 1));
    #pragma unroll
    for (int hh = 0; hh < 4; hh++) {
      const uint32_t bb = sb + (hh >> 1) * STAGE + (hh & 1) * 4096 + 2 * 8192;
      Half& h = R[hh];
      #pragma unroll
      for (int u = 0; u < 2; u++) {
        uint32_t a0, a1, a2, a3;
        if (u == 0) { XORZ(a0, h.x.x); XORZ(a1, h.y.x); XORZ(a2, h.x.y); XORZ(a3, h.y.y); }
        else        { XORZ(a0, h.x.z); XORZ(a1, h.y.z); XORZ(a2, h.x.w); XORZ(a3, h.y.w); }
        WG_FENCE(); wgmma_n128_hi(acc, a0, a1, a2, a3, make_desc(bb + u * 2048)); WG_COMMIT(); WG_WAIT(1);
        const int j = hh * 2 + u;
        #pragma unroll
        for (int z = 0; z < 8; z++) asm volatile("" : "+f"(acc[8 * j + z]) :: "memory");
        asm volatile("st.async.weak.shared::cluster.mbarrier::complete_tx::bytes.v4.b32 [%0], {%1,%2,%3,%4}, [%5];"
          :: "r"(rdst + j * 4096), "r"(pack_bf16(acc[8 * j], acc[8 * j + 1])), "r"(pack_bf16(acc[8 * j + 2], acc[8 * j + 3])),
             "r"(pack_bf16(acc[8 * j + 4], acc[8 * j + 5])), "r"(pack_bf16(acc[8 * j + 6], acc[8 * j + 7])), "r"(rbar) : "memory");
      }
    }
    WG_WAIT(0);
    fence_acc<64, 128>(acc);
    if (t == 0) STAMP(5);
    mbar_wait(sb + BAR_RECV + (c * 4 + w) * 8, 0);
    if (t == 0) STAMP(6);
    float s0a = 0.f, s0b = 0.f, s1a = 0.f, s1b = 0.f;
    #pragma unroll
    for (int j = 0; j < 8; j++) {
      uint32_t rv[4];
      asm volatile("ld.shared.v4.u32 {%0,%1,%2,%3}, [%4];" : "=r"(rv[0]), "=r"(rv[1]), "=r"(rv[2]), "=r"(rv[3]) : "r"(sb + OFF_RECV + j * 4096 + t * 16));
      #pragma unroll
      for (int m = 0; m < 2; m++) {
        float wa, wb;
        asm volatile("ld.shared.v2.f32 {%0,%1}, [%2];" : "=f"(wa), "=f"(wb) : "r"(sb + OFF_W2 + ((2 * j + m) * 8 + q * 2) * 4));
        #pragma unroll
        for (int e = 0; e < 4; e++) {
          const int a = 64 + 8 * j + 4 * m + e;
          const uint32_t pk = rv[2 * m + (e >> 1)];
          const float x = acc[a] + ((e & 1) ? bf_hi(pk) : bf_lo(pk));
          const float u = x * fmaf(x * x, 0.0356774081363001f, 0.7978845608028654f);
          float th; asm("tanh.approx.f32 %0, %1;" : "=f"(th) : "f"(u));
          const float aw = x * ((e & 1) ? wb : wa);
          if (e < 2) { s0a += aw; s0b = fmaf(aw, th, s0b); } else { s1a += aw; s1b = fmaf(aw, th, s1b); }
        }
      }
    }
    float s0 = s0a + s0b, s1 = s1a + s1b;
    s0 += __shfl_xor_sync(0xffffffffu, s0, 1); s1 += __shfl_xor_sync(0xffffffffu, s1, 1);
    s0 += __shfl_xor_sync(0xffffffffu, s0, 2); s1 += __shfl_xor_sync(0xffffffffu, s1, 2);
    if (t == 0) STAMP(7);
    const int me = nh * 2 + kh, owner = c * 2 + (w >> 1);
    const int rl = (w & 1) * 16 + g;
    if (owner == me) {
      if (q == 0) {
        asm volatile("st.shared.f32 [%0], %1;" :: "r"(sb + OFF_PART + rl * 4), "f"(s0) : "memory");
        asm volatile("st.shared.f32 [%0], %1;" :: "r"(sb + OFF_PART + (rl + 8) * 4), "f"(s1) : "memory");
      }
      asm volatile("bar.arrive 2, 96;" ::: "memory");
    } else if (q == 0) {
      unsigned long long* sl = g_slots + ((mt * 4 + owner) * 4 + me) * 32 + rl;
      asm volatile("st.relaxed.gpu.global.b64 [%0], %1;" :: "l"(sl), "l"((1ull << 32) | __float_as_uint(s0)) : "memory");
      asm volatile("st.relaxed.gpu.global.b64 [%0], %1;" :: "l"(sl + 8), "l"((1ull << 32) | __float_as_uint(s1)) : "memory");
    }
    }
  } else {
    const int w = warp, lane = tid & 31, g = lane >> 2, q = lane & 3;
    #pragma unroll
    for (int b = 0; b < 5; b++) {
      const int e2 = tid & 3, ln = (tid >> 2) & 31;
      const int gg = ln >> 2, col = (ln & 3) * 2 + (e2 & 1), hi = e2 >> 1;
      const int rg = hi ? (b == 0 || b == 3 ? 8 : (b == 4 ? 24 : 16)) : (b == 1 ? 8 : (b == 4 ? 16 : 0));
      const int cg = b == 0 ? 0 : (b == 1 ? 8 : (b == 2 ? 16 : 24));
      const int fi = rg + gg, fj = cg + col;
      float v = 0.f;
      if (fi < kF && fj < kF) {
        v = __bfloat162float(w_p[fi * kF + fj]);
        if (rg != cg) v += __bfloat162float(w_p[fj * kF + fi]);
      }
      asm volatile("st.shared.f32 [%0], %1;" :: "r"(sb + OFF_WTS + (b * 128 + tid) * 4), "f"(v) : "memory");
    }
    asm volatile("st.shared.f32 [%0], %1;" :: "r"(sb + OFF_W2 + tid * 4), "f"(0.5f * __bfloat162float(w2[nh * 256 + kh * 128 + tid])) : "memory");
    const float bias2 = __bfloat162float(b2[0]);
    __syncthreads();
    asm volatile("barrier.cluster.arrive.relaxed.aligned;" ::: "memory");
    asm volatile("setmaxnreg.dec.sync.aligned.u32 120;");
    const int me = nh * 2 + kh;
    mbar_wait(sb + BAR_IDX, 0);
    const uint32_t srow = sb + OFF_IDX + ((me * 32 + w * 8) * kF + g) * 4;
    const char *pa, *pb, *pc, *pe;
    auto setp = [&](int smp) {
      const uint32_t a = srow + smp * kF * 4;
      const uint32_t ia = lds32(a), ib = lds32(a + 32), ic = lds32(a + 64), ie = lds32(a + (g < 2 ? 96 : 0));
      pa = table + (size_t)(ia * 16u + q) * 16u; pb = table + (size_t)(ib * 16u + q) * 16u;
      pc = table + (size_t)(ic * 16u + q) * 16u; pe = table + (size_t)(ie * 16u + q) * 16u;
    };
    Quad L[2];
    L[0].e = make_uint4(0, 0, 0, 0); L[1].e = make_uint4(0, 0, 0, 0);
    auto ldq = [&](Quad& d, int quarter) {
      d.a = ldg128(pa + quarter * 64); d.b = ldg128(pb + quarter * 64); d.c = ldg128(pc + quarter * 64);
      if (g < 2) d.e = ldg128(pe + quarter * 64);
    };
    setp(0);
    ldq(L[0], 0); ldq(L[1], 1);
    #pragma unroll 1
    for (int smp = 0; smp < 8; smp++) {
      float G[5][4];
      #pragma unroll
      for (int b = 0; b < 5; b++) { G[b][0] = G[b][1] = G[b][2] = G[b][3] = 0.f; }
      #pragma unroll
      for (int j = 0; j < 4; j++) {
        Quad& d = L[j & 1];
        mma16816(G[0], d.a.x, d.b.x, d.a.y, d.b.y, d.a.x, d.a.y);
        mma16816(G[3], d.a.x, d.b.x, d.a.y, d.b.y, d.e.x, d.e.y);
        mma16816(G[1], d.b.x, d.c.x, d.b.y, d.c.y, d.b.x, d.b.y);
        mma16816(G[2], d.a.x, d.c.x, d.a.y, d.c.y, d.c.x, d.c.y);
        mma16816(G[4], d.c.x, d.e.x, d.c.y, d.e.y, d.e.x, d.e.y);
        mma16816(G[0], d.a.z, d.b.z, d.a.w, d.b.w, d.a.z, d.a.w);
        mma16816(G[3], d.a.z, d.b.z, d.a.w, d.b.w, d.e.z, d.e.w);
        mma16816(G[1], d.b.z, d.c.z, d.b.w, d.c.w, d.b.z, d.b.w);
        mma16816(G[2], d.a.z, d.c.z, d.a.w, d.c.w, d.c.z, d.c.w);
        mma16816(G[4], d.c.z, d.e.z, d.c.w, d.e.w, d.e.z, d.e.w);
        if (j == 2) setp(min(smp + 1, 7));
        ldq(d, (j + 2) & 3);
      }
      float sum = 0.f;
      #pragma unroll
      for (int b = 0; b < 5; b++) {
        float4 wv;
        asm volatile("ld.shared.v4.f32 {%0,%1,%2,%3}, [%4];" : "=f"(wv.x), "=f"(wv.y), "=f"(wv.z), "=f"(wv.w) : "r"(sb + OFF_WTS + (b * 32 + lane) * 16));
        sum = fmaf(G[b][0], wv.x, sum); sum = fmaf(G[b][1], wv.y, sum); sum = fmaf(G[b][2], wv.z, sum); sum = fmaf(G[b][3], wv.w, sum);
      }
      #pragma unroll
      for (int o = 16; o > 0; o >>= 1) sum += __shfl_xor_sync(0xffffffffu, sum, o);
      if (lane == 0) asm volatile("st.shared.f32 [%0], %1;" :: "r"(sb + OFF_PART + 128 + (w * 8 + smp) * 4), "f"(sum) : "memory");
    }
    if (tid == 0) STAMP(8);
    asm volatile("barrier.cluster.wait.aligned;" ::: "memory");
    asm volatile("bar.sync 1, 128;" ::: "memory");
    if (w == 0) {
      float v = bias2;
      { float pv; asm volatile("ld.shared.f32 %0, [%1];" : "=f"(pv) : "r"(sb + OFF_PART + 128 + lane * 4)); v += pv; }
      asm volatile("bar.sync 2, 96;" ::: "memory");
      { float pv; asm volatile("ld.shared.f32 %0, [%1];" : "=f"(pv) : "r"(sb + OFF_PART + lane * 4)); v += pv; }
      unsigned long long* sl = g_slots + ((mt * 4 + me) * 4) * 32 + lane;
      #pragma unroll
      for (int src = 0; src < 4; src++) {
        if (src == me) continue;
        unsigned long long u; int it = 0;
        do { asm volatile("ld.relaxed.gpu.global.b64 %0, [%1];" : "=l"(u) : "l"(sl + src * 32) : "memory"); if (++it > 4000000) __trap(); } while ((u >> 32) == 0);
        v += __uint_as_float((uint32_t)u);
        asm volatile("st.relaxed.gpu.global.b64 [%0], %1;" :: "l"(sl + src * 32), "l"(0ull) : "memory");
      }
      out[mt * 128 + me * 32 + lane] = __float2bfloat16(v);
      if (lane == 0) { STAMP(9); GSTAMP(10); }
    }
  }
}

typedef CUresult (*EncodeFn)(CUtensorMap*, CUtensorMapDataType, cuuint32_t, void*, const cuuint64_t*, const cuuint64_t*, const cuuint32_t*,
                             const cuuint32_t*, CUtensorMapInterleave, CUtensorMapSwizzle, CUtensorMapL2promotion, CUtensorMapFloatOOBfill);
}

extern "C" void kernel_launch(void* const* d_in, const int* in_sizes, int n_in, void* d_out, int out_size) {
  (void)in_sizes; (void)n_in; (void)out_size;
  static EncodeFn enc = nullptr;
  if (!enc) {
    void* fn = nullptr; cudaDriverEntryPointQueryResult qr;
    cudaGetDriverEntryPoint("cuTensorMapEncodeTiled", &fn, cudaEnableDefault, &qr);
    enc = (EncodeFn)fn;
    cudaFuncSetAttribute(pnn_mlp_kernel, cudaFuncAttributeMaxDynamicSharedMemorySize, SMEM_BYTES);
  }
  CUtensorMap tm;
  cuuint64_t dims[5] = {512, 2, 4, 4, 104};
  cuuint64_t strides[4] = {1024, 8 * 1024, 2 * 1024, 32 * 1024};
  cuuint32_t box[5] = {64, 2, 4, 4, 2};
  cuuint32_t es[5] = {1, 1, 1, 1, 1};
  enc(&tm, CU_TENSOR_MAP_DATA_TYPE_BFLOAT16, 5, d_in[3], dims, strides, box, es, CU_TENSOR_MAP_INTERLEAVE_NONE, CU_TENSOR_MAP_SWIZZLE_128B,
      CU_TENSOR_MAP_L2_PROMOTION_L2_128B, CU_TENSOR_MAP_FLOAT_OOB_FILL_NONE);
  cudaLaunchConfig_t cfg = {};
  cfg.gridDim = dim3(128); cfg.blockDim = dim3(384); cfg.dynamicSmemBytes = SMEM_BYTES; cfg.stream = cudaStreamPerThread;
  cudaLaunchAttribute at[1];
  at[0].id = cudaLaunchAttributeClusterDimension; at[0].val.clusterDim.x = 2; at[0].val.clusterDim.y = 1; at[0].val.clusterDim.z = 1;
  cfg.attrs = at; cfg.numAttrs = 1;
  cudaLaunchKernelEx(&cfg, pnn_mlp_kernel, tm, (const int*)d_in[0], (const char*)d_in[1], (const __nv_bfloat16*)d_in[2],
                     (const __nv_bfloat16*)d_in[4], (const __nv_bfloat16*)d_in[5], (const __nv_bfloat16*)d_in[6], (__nv_bfloat16*)d_out, 0u);
}
```

```cpp
#include <cuda_runtime.h>
#include <cuda_bf16.h>
#include <cuda.h>
#include <stdint.h>

#define NPNN 8
#define PFD 3
#define PNGO 1
#define NSTAT_V 8
#define PNLATE 1
#define PNR 2
#define PNDELAY 1
#define PNPF 1
namespace {

constexpr int kB = 4096, kF = 26, kD = 128, kH = 512;
constexpr int NST = 4;
constexpr uint32_t STAGE = 32768;
constexpr uint32_t PCELL = 16384;
constexpr uint32_t OFF_RECV = NST * STAGE;
constexpr uint32_t OFF_STAT = OFF_RECV + 32768;
constexpr uint32_t OFF_IDX  = OFF_STAT + PCELL;
constexpr uint32_t OFF_WTS  = OFF_IDX + 128 * kF * 4;
constexpr uint32_t OFF_W2   = OFF_WTS + 4096;
constexpr uint32_t OFF_PART = OFF_W2 + 512;
constexpr uint32_t OFF_TRC  = OFF_PART + 384;
constexpr uint32_t OFF_BAR  = OFF_TRC + 112;
constexpr uint32_t SMEM_USED = OFF_BAR + 58 * 8;
static_assert(SMEM_USED <= 199680, "keep the 196 KB carve-out (60 KB of L1)");
constexpr uint32_t SMEM_BYTES = SMEM_USED;
constexpr uint32_t BAR_FULL = OFF_BAR, BAR_EMPTY = OFF_BAR + 32, BAR_IDX = OFF_BAR + 64, BAR_RECV = OFF_BAR + 72;
constexpr uint32_t BAR_GO = OFF_BAR + 136, BAR_FREE2 = OFF_BAR + 144, BAR_FREE3 = OFF_BAR + 152, BAR_FREE01 = OFF_BAR + 160;
constexpr uint32_t BAR_PFULL = OFF_BAR + 168, BAR_PDONE = BAR_PFULL + 16 * 8, BAR_PALL = BAR_PDONE + 16 * 8, BAR_FREES = BAR_PALL + 8, OFF_QUEUE = BAR_FREES + 8;
#define NHELP_V 0
constexpr int NHELP = NHELP_V;
constexpr int OWN = NHELP ? 26 : 32, NPAIR = OWN / 2;
constexpr int NEXT = NHELP ? 32 - OWN : 1;

__device__ unsigned long long g_slots[32 * 4 * 4 * 32];
__device__ unsigned long long g_pnn[4096];
#define STAMP(i)
#define GSTAMP(i)

__device__ __forceinline__ void wgmma_n128_lo(float (&d)[128], uint32_t a0, uint32_t a1, uint32_t a2, uint32_t a3, uint32_t dlo) {
  asm volatile("{\n.reg .b64 db;\nmov.b64 db, {%68, 0x40000040};\n"
    "wgmma.mma_async.sync.aligned.m64n128k16.f32.bf16.bf16 "
    "{%0, %1, %2, %3, %4, %5, %6, %7, %8, %9, %10, %11, %12, %13, %14, %15, %16, %17, %18, %19, %20, %21, %22, %23, %24, %25, %26, %27, %28, %29, %30, %31, %32, %33, %34, %35, %36, %37, %38, %39, %40, %41, %42, %43, %44, %45, %46, %47, %48, %49, %50, %51, %52, %53, %54, %55, %56, %57, %58, %59, %60, %61, %62, %63}, "
    "{%64, %65, %66, %67}, db, 1, 1, 1, 1;\n}\n"
    : "+f"(d[0]), "+f"(d[1]), "+f"(d[2]), "+f"(d[3]), "+f"(d[4]), "+f"(d[5]), "+f"(d[6]), "+f"(d[7]), "+f"(d[8]), "+f"(d[9]), "+f"(d[10]), "+f"(d[11]), "+f"(d[12]), "+f"(d[13]), "+f"(d[14]), "+f"(d[15]), "+f"(d[16]), "+f"(d[17]), "+f"(d[18]), "+f"(d[19]), "+f"(d[20]), "+f"(d[21]), "+f"(d[22]), "+f"(d[23]), "+f"(d[24]), "+f"(d[25]), "+f"(d[26]), "+f"(d[27]), "+f"(d[28]), "+f"(d[29]), "+f"(d[30]), "+f"(d[31]), "+f"(d[32]), "+f"(d[33]), "+f"(d[34]), "+f"(d[35]), "+f"(d[36]), "+f"(d[37]), "+f"(d[38]), "+f"(d[39]), "+f"(d[40]), "+f"(d[41]), "+f"(d[42]), "+f"(d[43]), "+f"(d[44]), "+f"(d[45]), "+f"(d[46]), "+f"(d[47]), "+f"(d[48]), "+f"(d[49]), "+f"(d[50]), "+f"(d[51]), "+f"(d[52]), "+f"(d[53]), "+f"(d[54]), "+f"(d[55]), "+f"(d[56]), "+f"(d[57]), "+f"(d[58]), "+f"(d[59]), "+f"(d[60]), "+f"(d[61]), "+f"(d[62]), "+f"(d[63])
    : "r"(a0), "r"(a1), "r"(a2), "r"(a3), "r"(dlo));
}
__device__ __forceinline__ void wgmma_n128_hi(float (&d)[128], uint32_t a0, uint32_t a1, uint32_t a2, uint32_t a3, uint32_t dlo) {
  asm volatile("{\n.reg .b64 db;\nmov.b64 db, {%68, 0x40000040};\n"
    "wgmma.mma_async.sync.aligned.m64n128k16.f32.bf16.bf16 "
    "{%0, %1, %2, %3, %4, %5, %6, %7, %8, %9, %10, %11, %12, %13, %14, %15, %16, %17, %18, %19, %20, %21, %22, %23, %24, %25, %26, %27, %28, %29, %30, %31, %32, %33, %34, %35, %36, %37, %38, %39, %40, %41, %42, %43, %44, %45, %46, %47, %48, %49, %50, %51, %52, %53, %54, %55, %56, %57, %58, %59, %60, %61, %62, %63}, "
    "{%64, %65, %66, %67}, db, 1, 1, 1, 1;\n}\n"
    : "+f"(d[64]), "+f"(d[65]), "+f"(d[66]), "+f"(d[67]), "+f"(d[68]), "+f"(d[69]), "+f"(d[70]), "+f"(d[71]), "+f"(d[72]), "+f"(d[73]), "+f"(d[74]), "+f"(d[75]), "+f"(d[76]), "+f"(d[77]), "+f"(d[78]), "+f"(d[79]), "+f"(d[80]), "+f"(d[81]), "+f"(d[82]), "+f"(d[83]), "+f"(d[84]), "+f"(d[85]), "+f"(d[86]), "+f"(d[87]), "+f"(d[88]), "+f"(d[89]), "+f"(d[90]), "+f"(d[91]), "+f"(d[92]), "+f"(d[93]), "+f"(d[94]), "+f"(d[95]), "+f"(d[96]), "+f"(d[97]), "+f"(d[98]), "+f"(d[99]), "+f"(d[100]), "+f"(d[101]), "+f"(d[102]), "+f"(d[103]), "+f"(d[104]), "+f"(d[105]), "+f"(d[106]), "+f"(d[107]), "+f"(d[108]), "+f"(d[109]), "+f"(d[110]), "+f"(d[111]), "+f"(d[112]), "+f"(d[113]), "+f"(d[114]), "+f"(d[115]), "+f"(d[116]), "+f"(d[117]), "+f"(d[118]), "+f"(d[119]), "+f"(d[120]), "+f"(d[121]), "+f"(d[122]), "+f"(d[123]), "+f"(d[124]), "+f"(d[125]), "+f"(d[126]), "+f"(d[127])
    : "r"(a0), "r"(a1), "r"(a2), "r"(a3), "r"(dlo));
}

__device__ __forceinline__ uint32_t smem_u32(const void* p) { return (uint32_t)__cvta_generic_to_shared(p); }
__device__ __forceinline__ void mbar_init(uint32_t bar, uint32_t cnt) { asm volatile("mbarrier.init.shared::cta.b64 [%0], %1;" :: "r"(bar), "r"(cnt)); }
__device__ __forceinline__ void mbar_expect_tx(uint32_t bar, uint32_t bytes) { asm volatile("mbarrier.arrive.expect_tx.shared::cta.b64 _, [%0], %1;" :: "r"(bar), "r"(bytes) : "memory"); }
__device__ __forceinline__ void mbar_arrive(uint32_t bar) { asm volatile("mbarrier.arrive.shared::cta.b64 _, [%0];" :: "r"(bar) : "memory"); }
__device__ __forceinline__ void mbar_wait(uint32_t bar, uint32_t parity) {
  asm volatile("{\n.reg .pred p;\n.reg .u32 c;\nmov.u32 c, 0;\n"
    "LAB_WAIT:\nmbarrier.try_wait.parity.shared::cta.b64 p, [%0], %1;\n@p bra.uni LAB_DONE;\n"
    "add.u32 c, c, 1;\nsetp.lt.u32 p, c, 4000000;\n@p bra.uni LAB_WAIT;\ntrap;\nLAB_DONE:\n}" :: "r"(bar), "r"(parity) : "memory");
}
__device__ __forceinline__ uint32_t desc_lo(uint32_t addr) { return ((addr & 0x3FFFF) >> 4) | ((8192u >> 4) << 16); }
__device__ __forceinline__ uint4 ldg128(const void* p) {
  uint4 v;
  asm volatile("ld.global.nc.L1::no_allocate.v4.u32 {%0,%1,%2,%3}, [%4];" : "=r"(v.x), "=r"(v.y), "=r"(v.z), "=r"(v.w) : "l"(p));
  return v;
}
__device__ __forceinline__ uint32_t lds32(uint32_t a) { uint32_t v; asm volatile("ld.shared.u32 %0, [%1];" : "=r"(v) : "r"(a)); return v; }
__device__ __forceinline__ void tma_w1(uint32_t dst, const CUtensorMap* tm, uint32_t bar, int x, int kb) {
  asm volatile("cp.async.bulk.tensor.5d.shared::cluster.global.mbarrier::complete_tx::bytes [%0], [%1, {%3, %4, %4, %4, %5}], [%2];"
    :: "r"(dst), "l"(tm), "r"(bar), "r"(x), "r"(0), "r"(kb) : "memory");
}
__device__ __forceinline__ float bf_lo(uint32_t v) { return __uint_as_float(v << 16); }
__device__ __forceinline__ float bf_hi(uint32_t v) { return __uint_as_float(v & 0xffff0000u); }
__device__ __forceinline__ uint32_t pack_bf16(float lo, float hi) { uint32_t r; asm("cvt.rn.bf16x2.f32 %0, %1, %2;" : "=r"(r) : "f"(hi), "f"(lo)); return r; }
__device__ __forceinline__ void mma16816(float (&d)[4], uint32_t a0, uint32_t a1, uint32_t a2, uint32_t a3, uint32_t b0, uint32_t b1) {
  asm volatile("mma.sync.aligned.m16n8k16.row.col.f32.bf16.bf16.f32 {%0,%1,%2,%3}, {%4,%5,%6,%7}, {%8,%9}, {%0,%1,%2,%3};"
    : "+f"(d[0]), "+f"(d[1]), "+f"(d[2]), "+f"(d[3]) : "r"(a0), "r"(a1), "r"(a2), "r"(a3), "r"(b0), "r"(b1));
}

__device__ __forceinline__ uint32_t rd_tid() { uint32_t v; asm volatile("mov.u32 %0, %tid.x;" : "=r"(v)); return v; }
__device__ __forceinline__ uint32_t rd_cta() { uint32_t v; asm volatile("mov.u32 %0, %ctaid.x;" : "=r"(v)); return v; }
template <int LO, int HI> __device__ __forceinline__ void fence_acc(float (&d)[128]) {
  #pragma unroll
  for (int i = LO; i < HI; i++) asm volatile("" : "+f"(d[i]) :: "memory");
}
__device__ __forceinline__ bool elect_one() {
  uint32_t p; asm volatile("{\n.reg .pred P;\nelect.sync _|P, 0xffffffff;\nselp.u32 %0, 1, 0, P;\n}" : "=r"(p)); return p != 0;
}
constexpr int NSTAT = NSTAT_V;
__device__ __forceinline__ void cp16(uint32_t dst, const void* src) { asm volatile("cp.async.cg.shared.global [%0], [%1], 16;" :: "r"(dst), "l"(src) : "memory"); }
__device__ __forceinline__ uint32_t pnn_cell(uint32_t sb, int p) {
  if (p < NSTAT) return sb + OFF_STAT;
  p = (p - NSTAT) & 7;
  return p < 4 ? sb + (p + 4) * PCELL : sb + (p & 1) * 2 * PCELL + (p >= 6 ? PCELL : 0);
}
__device__ __forceinline__ uint32_t pnn_gate(int p) {
  if (p == 0) return BAR_GO;
  if (p < NSTAT) return BAR_PDONE + (p - 1) * 8;
  const int j = p - NSTAT;
  return j < 2 ? BAR_FREE2 : (j < 4 ? BAR_FREE3 : (j < 6 ? BAR_FREES : (j < 8 ? BAR_FREE01 : BAR_PDONE + (p - 8) * 8)));
}
__device__ __forceinline__ void wgmma_gram(float (&d)[32], uint32_t dlo, int acc) {
  asm volatile("{\n.reg .pred p;\n.reg .b64 db;\nsetp.ne.b32 p, %33, 0;\nmov.b64 db, {%32, 0x40000040};\n"
    "wgmma.mma_async.sync.aligned.m64n64k16.f32.bf16.bf16 "
    "{%0,%1,%2,%3,%4,%5,%6,%7,%8,%9,%10,%11,%12,%13,%14,%15,%16,%17,%18,%19,%20,%21,%22,%23,%24,%25,%26,%27,%28,%29,%30,%31}, db, db, p, 1, 1, 0, 0;\n}\n"
    : "+f"(d[0]), "+f"(d[1]), "+f"(d[2]), "+f"(d[3]), "+f"(d[4]), "+f"(d[5]), "+f"(d[6]), "+f"(d[7]),
      "+f"(d[8]), "+f"(d[9]), "+f"(d[10]), "+f"(d[11]), "+f"(d[12]), "+f"(d[13]), "+f"(d[14]), "+f"(d[15]),
      "+f"(d[16]), "+f"(d[17]), "+f"(d[18]), "+f"(d[19]), "+f"(d[20]), "+f"(d[21]), "+f"(d[22]), "+f"(d[23]),
      "+f"(d[24]), "+f"(d[25]), "+f"(d[26]), "+f"(d[27]), "+f"(d[28]), "+f"(d[29]), "+f"(d[30]), "+f"(d[31])
    : "r"(dlo), "r"(acc));
}

__device__ __forceinline__ void pnn_issue(float (&D)[32], uint32_t sb, int p) {
  mbar_wait(sb + BAR_PFULL + p * 8, 0);
  asm volatile("fence.proxy.async.shared::cta;" ::: "memory");
  const uint32_t dl = ((pnn_cell(sb, p) & 0x3FFFF) >> 4) | (1u << 16);
  asm volatile("wgmma.fence.sync.aligned;" ::: "memory");
  #pragma unroll
  for (int kk = 0; kk < 8; kk++) wgmma_gram(D, dl + (((kk >> 2) * 8192 + (kk & 3) * 32) >> 4), kk > 0);
  asm volatile("wgmma.commit_group.sync.aligned;" ::: "memory");
}
__device__ __forceinline__ float pnn_dot(float (&D)[32], const float (&wt)[16], int w, int lane) {
  const bool pc = (lane & 3) == 0, pr = !(w & 1) || lane < 8;
  #pragma unroll
  for (int i = 0; i < 32; i++) asm volatile("" : "+f"(D[i]) :: "memory");
  float s4[4] = {0.f, 0.f, 0.f, 0.f};
  if (w >> 1) {
    #pragma unroll
    for (int i = 0; i < 16; i++) { const bool ok = ((i >> 2) < 3 || pc) && ((i & 2) == 0 || pr); if (ok) s4[i & 3] = fmaf(D[16 + i], wt[i], s4[i & 3]); }
  } else {
    #pragma unroll
    for (int i = 0; i < 16; i++) { const bool ok = ((i >> 2) < 3 || pc) && ((i & 2) == 0 || pr); if (ok) s4[i & 3] = fmaf(D[i], wt[i], s4[i & 3]); }
  }
  return (s4[0] + s4[1]) + (s4[2] + s4[3]);
}
__device__ __forceinline__ void pnn_store(uint32_t sb, float sum, int w, int lane, int p) {
  if (lane == 0) {
    asm volatile("st.shared.f32 [%0], %1;" :: "r"(sb + OFF_PART + 128 + ((2 * p + (w >> 1)) * 2 + (w & 1)) * 4), "f"(sum) : "memory");
    mbar_arrive(sb + BAR_PALL);
  }
}
__device__ __forceinline__ void pnn_pair(uint32_t sb, const float (&wt)[16], int w, int lane, int p) {
  float D[32];
  pnn_issue(D, sb, p);
  asm volatile("wgmma.wait_group.sync.aligned 0;" ::: "memory");
  if (w == 0 && lane == 0) mbar_arrive(sb + BAR_PDONE + p * 8);
  float sum = pnn_dot(D, wt, w, lane);
  #pragma unroll
  for (int o = 16; o > 0; o >>= 1) sum += __shfl_xor_sync(0xffffffffu, sum, o);
  pnn_store(sb, sum, w, lane, p);
}
__device__ __forceinline__ void pnn_triple(uint32_t sb, const float (&wt)[16], int w, int lane, int p) {
  float D0[32], D1[32], D2[32];
  pnn_issue(D0, sb, p); pnn_issue(D1, sb, p + 3); pnn_issue(D2, sb, p + 6);
  asm volatile("wgmma.wait_group.sync.aligned 2;" ::: "memory");
  float a = pnn_dot(D0, wt, w, lane);
  asm volatile("wgmma.wait_group.sync.aligned 1;" ::: "memory");
  float b = pnn_dot(D1, wt, w, lane);
  asm volatile("wgmma.wait_group.sync.aligned 0;" ::: "memory");
  float c = pnn_dot(D2, wt, w, lane);
  #pragma unroll
  for (int o = 16; o > 0; o >>= 1) { a += __shfl_xor_sync(0xffffffffu, a, o); b += __shfl_xor_sync(0xffffffffu, b, o); c += __shfl_xor_sync(0xffffffffu, c, o); }
  pnn_store(sb, a, w, lane, p); pnn_store(sb, b, w, lane, p + 3); pnn_store(sb, c, w, lane, p + 6);
}
__device__ __forceinline__ void pnn_load_weights(float (&wt)[16], const __nv_bfloat16* __restrict__ w_p, int w, int lane) {
  #pragma unroll
  for (int i = 0; i < 16; i++) {
    const int fi = (w & 1) * 16 + (lane >> 2) + 8 * ((i >> 1) & 1), fj = 8 * (i >> 2) + 2 * (lane & 3) + (i & 1);
    wt[i] = (fi < kF && fj < kF) ? __bfloat162float(w_p[fi * kF + fj]) : 0.f;
  }
}

struct Half { uint4 x, y; };

__global__ void __cluster_dims__(2, 1, 1) __launch_bounds__(512, 1)
pnn_mlp_kernel(const __grid_constant__ CUtensorMap tmW, const int* __restrict__ idx, const char* __restrict__ table,
               const __nv_bfloat16* __restrict__ w_p, const __nv_bfloat16* __restrict__ b1, const __nv_bfloat16* __restrict__ w2,
               const __nv_bfloat16* __restrict__ b2, __nv_bfloat16* __restrict__ out, uint32_t zero) {
  extern __shared__ __align__(1024) uint8_t smem_raw[];
  const uint32_t sb = smem_u32(smem_raw);
  if (sb & 1023u) __trap();
  const int tid = threadIdx.x;
  const int warp = __shfl_sync(0xffffffffu, tid >> 5, 0);
  const int bid = blockIdx.x - NHELP;
  const int kh = bid & 1, pair = bid >> 1, nh = pair & 1, mt = pair >> 1;
  const int f0 = kh * 13;

  if (tid == 0) {
    STAMP(0); GSTAMP(1);
    mbar_init(sb + BAR_IDX, 1);
    #pragma unroll
    for (int s = 0; s < NST; s++) { mbar_init(sb + BAR_FULL + s * 8, 1); mbar_init(sb + BAR_EMPTY + s * 8, 2); }
    #pragma unroll
    for (int w = 0; w < 8; w++) mbar_init(sb + BAR_RECV + w * 8, 1);
    #pragma unroll
    for (int p = 0; p < NPAIR; p++) mbar_init(sb + BAR_PFULL + p * 8, 32);
    #pragma unroll
    for (int p = 0; p < 16; p++) mbar_init(sb + BAR_PDONE + p * 8, 1);
    mbar_init(sb + BAR_PALL, 4 * NPAIR); mbar_init(sb + BAR_FREES, 2);
    asm volatile("st.shared.u32 [%0], %1;" :: "r"(sb + OFF_QUEUE), "r"(0u) : "memory");
    mbar_init(sb + BAR_GO, 1); mbar_init(sb + BAR_FREE2, 2); mbar_init(sb + BAR_FREE3, 2); mbar_init(sb + BAR_FREE01, 2);
    asm volatile("fence.mbarrier_init.release.cluster;" ::: "memory");
    mbar_expect_tx(sb + BAR_IDX, 128 * kF * 4);
    asm volatile("cp.async.bulk.shared::cluster.global.mbarrier::complete_tx::bytes [%0], [%1], %2, [%3];"
      :: "r"(sb + OFF_IDX), "l"(idx + (size_t)mt * 128 * kF), "r"(128 * kF * 4), "r"(sb + BAR_IDX) : "memory");
  }

  if (warp >= 4 && warp < 12) {
    const int t = tid - 128, c = (warp - 4) >> 2, w = warp & 3, lane = tid & 31, g = lane >> 2, q = lane & 3;
    const int r0 = c * 64 + w * 16 + g;
    const int* ip = idx + (size_t)(mt * 128 + r0) * kF + f0;
    const uint32_t i00 = __ldg(ip), i10 = __ldg(ip + 8 * kF), i01 = __ldg(ip + 1), i11 = __ldg(ip + 8 * kF + 1);
    uint32_t braw[16];
    {
      const uint32_t* bp = reinterpret_cast<const uint32_t*>(b1 + nh * 256 + kh * 128) + q;
      #pragma unroll
      for (int i = 0; i < 16; i++) braw[i] = __ldg(bp + i * 4);
    }
    asm volatile("bar.sync 0, 512;" ::: "memory");
    if (t == 0) STAMP(11);
    asm volatile("barrier.cluster.arrive.relaxed.aligned;" ::: "memory");
    asm volatile("setmaxnreg.inc.sync.aligned.u32 192;");
    if (t == 0) STAMP(12);
    if (t == 0) STAMP(13);
    if (elect_one()) mbar_expect_tx(sb + BAR_RECV + (c * 4 + w) * 8, 4096);

    Half R[4];
    const char *p0, *p1;
    auto setptr = [&](uint32_t i0, uint32_t i1) {
      const uint32_t qq = rd_tid() & 3;
      p0 = table + (size_t)(i0 * 16u + qq) * 16u; p1 = table + (size_t)(i1 * 16u + qq) * 16u;
    };
    auto refill = [&](Half& h, int quarter) { h.x = ldg128(p0 + quarter * 64); h.y = ldg128(p1 + quarter * 64); };
    setptr(i00, i10);
    refill(R[0], 0); refill(R[1], 1); refill(R[2], 2); refill(R[3], 3);
    setptr(i01, i11);

    float acc[128];
    #pragma unroll
    for (int i = 0; i < 64; i++) acc[i] = 0.f;
    #pragma unroll
    for (int i = 0; i < 16; i++) {
      acc[64 + 4 * i + 0] = bf_lo(braw[i]); acc[64 + 4 * i + 1] = bf_hi(braw[i]);
      acc[64 + 4 * i + 2] = bf_lo(braw[i]); acc[64 + 4 * i + 3] = bf_hi(braw[i]);
    }
    fence_acc<0, 128>(acc);
    const uint32_t sidx0 = sb + OFF_IDX + (r0 * kF + f0) * 4;
    mbar_wait(sb + BAR_IDX, 0);
    if (t == 0) STAMP(2);

#define FRAG(h, u, v) uint32_t f0_ = h.x.u ^ zero, f1_ = h.y.u ^ zero, f2_ = h.x.v ^ zero, f3_ = h.y.v ^ zero
#define WG_FENCE()  asm volatile("wgmma.fence.sync.aligned;" ::: "memory")
#define WG_COMMIT() asm volatile("wgmma.commit_group.sync.aligned;" ::: "memory")
#define WG_WAIT(n)  asm volatile("wgmma.wait_group.sync.aligned " #n ";" ::: "memory")
#define XORZ(d, s)  asm volatile("xor.b32 %0, %1, %2;" : "=r"(d) : "r"(s), "r"(zero))
    const uint32_t dbase = desc_lo(sb);
    auto mma256 = [&](uint32_t x0, uint32_t y0, uint32_t x1, uint32_t y1, uint32_t off) {
      uint32_t a0, a1, a2, a3;
      XORZ(a0, x0); XORZ(a1, y0); XORZ(a2, x1); XORZ(a3, y1);
      WG_FENCE(); wgmma_n128_lo(acc, a0, a1, a2, a3, dbase + (off >> 4)); wgmma_n128_hi(acc, a0, a1, a2, a3, dbase + ((off + 2 * 8192) >> 4)); WG_COMMIT();
    };
    uint32_t ni0 = 0, ni1 = 0;
    uint32_t sidx = sidx0 + 8;
    #pragma unroll 1
    for (int f = 0; f < 12; f++) {
      const uint32_t odd = f & 1, ph = (f >> 1) & 1;
      const uint32_t db = dbase + odd * (2 * STAGE >> 4);
      const uint32_t bfull = sb + BAR_FULL + odd * 16;
      #pragma unroll
      for (int j = 0; j < 4; j++) {
        Half& h = R[j];
        if ((j & 1) == 0) mbar_wait(bfull + (j >> 1) * 8, ph);
        const uint32_t off = (j >> 1) * STAGE + (j & 1) * 4096;
        {
          uint32_t a0, a1, a2, a3, b0, b1_, b2_, b3;
          XORZ(a0, h.x.x); XORZ(a1, h.y.x); XORZ(a2, h.x.y); XORZ(a3, h.y.y);
          XORZ(b0, h.x.z); XORZ(b1_, h.y.z); XORZ(b2_, h.x.w); XORZ(b3, h.y.w);
          WG_FENCE();
          wgmma_n128_lo(acc, a0, a1, a2, a3, db + (off >> 4));
          wgmma_n128_hi(acc, a0, a1, a2, a3, db + ((off + 2 * 8192) >> 4));
          wgmma_n128_lo(acc, b0, b1_, b2_, b3, db + ((off + 2048) >> 4));
          wgmma_n128_hi(acc, b0, b1_, b2_, b3, db + ((off + 2048 + 2 * 8192) >> 4));
          WG_COMMIT();
        }
        refill(h, j);
        if (j == 2) {
          ni0 = lds32(sidx); ni1 = lds32(sidx + 8 * kF * 4);
          if (f < 10) sidx += 4;
        }
        if (j == 3) setptr(ni0, ni1);
        WG_WAIT(1);
        if (j == 0) { if (w == 0 && f > 0) { if (elect_one()) mbar_arrive(sb + BAR_EMPTY + (odd ^ 1) * 16 + 8); } }
        if (j == 2) { if (w == 0) { if (elect_one()) { mbar_arrive(sb + BAR_EMPTY + odd * 16); if (f == 11) mbar_arrive(sb + BAR_FREE2); if (f == PNGO && c == 0) mbar_arrive(sb + BAR_GO); } } }
      }
    }
    WG_WAIT(0);
    if (w == 0) { if (elect_one()) mbar_arrive(sb + BAR_FREE3); }
    {
    const uint32_t tid2 = rd_tid();
    const int t = tid2 - 128, lane = t & 31, g = lane >> 2, q = lane & 3;
    if (t == 0) STAMP(4);
    mbar_wait(sb + BAR_FULL + 0, 0);
    mbar_wait(sb + BAR_FULL + 8, 0);
    #pragma unroll
    for (int hh = 0; hh < 4; hh++) {
      const uint32_t bb = dbase + (((hh >> 1) * STAGE + (hh & 1) * 4096) >> 4);
      Half& h = R[hh];
      { uint32_t a0, a1, a2, a3; XORZ(a0, h.x.x); XORZ(a1, h.y.x); XORZ(a2, h.x.y); XORZ(a3, h.y.y);
        WG_FENCE(); wgmma_n128_lo(acc, a0, a1, a2, a3, bb); WG_COMMIT(); WG_WAIT(1); }
      { uint32_t a0, a1, a2, a3; XORZ(a0, h.x.z); XORZ(a1, h.y.z); XORZ(a2, h.x.w); XORZ(a3, h.y.w);
        WG_FENCE(); wgmma_n128_lo(acc, a0, a1, a2, a3, bb + (2048 >> 4)); WG_COMMIT(); WG_WAIT(1); }
    }
    asm volatile("barrier.cluster.wait.aligned;" ::: "memory");
    uint32_t rdst, rbar;
    asm("mapa.shared::cluster.u32 %0, %1, %2;" : "=r"(rdst) : "r"(sb + OFF_RECV + t * 16), "r"(kh ^ 1));
    asm("mapa.shared::cluster.u32 %0, %1, %2;" : "=r"(rbar) : "r"(sb + BAR_RECV + (c * 4 + w) * 8), "r"(kh ^ 1));
    {
      uint32_t fr[8][4];
      #pragma unroll
      for (int hh = 0; hh < 4; hh++) {
        Half& h = R[hh];
        XORZ(fr[2 * hh][0], h.x.x); XORZ(fr[2 * hh][1], h.y.x); XORZ(fr[2 * hh][2], h.x.y); XORZ(fr[2 * hh][3], h.y.y);
        XORZ(fr[2 * hh + 1][0], h.x.z); XORZ(fr[2 * hh + 1][1], h.y.z); XORZ(fr[2 * hh + 1][2], h.x.w); XORZ(fr[2 * hh + 1][3], h.y.w);
      }
      WG_FENCE();
      #pragma unroll
      for (int v = 0; v < 8; v++)
        wgmma_n128_hi(acc, fr[v][0], fr[v][1], fr[v][2], fr[v][3], dbase + ((((v >> 2) * STAGE + ((v >> 1) & 1) * 4096 + (v & 1) * 2048 + 2 * 8192)) >> 4));
      WG_COMMIT();
      WG_WAIT(1);
      if (w == 0) { if (elect_one()) mbar_arrive(sb + BAR_FREES); }
      fence_acc<0, 64>(acc);
      auto ship = [&](int j) {
        asm volatile("st.async.weak.shared::cluster.mbarrier::complete_tx::bytes.v4.b32 [%0], {%1,%2,%3,%4}, [%5];"
          :: "r"(rdst + j * 4096), "r"(pack_bf16(acc[8 * j], acc[8 * j + 1])), "r"(pack_bf16(acc[8 * j + 2], acc[8 * j + 3])),
             "r"(pack_bf16(acc[8 * j + 4], acc[8 * j + 5])), "r"(pack_bf16(acc[8 * j + 6], acc[8 * j + 7])), "r"(rbar) : "memory");
      };
      ship(0); ship(1); ship(2); ship(3);
      WG_WAIT(0);
      if (w == 0) { if (elect_one()) mbar_arrive(sb + BAR_FREE01); }
      ship(4); ship(5); ship(6); ship(7);
    }
    fence_acc<64, 128>(acc);
    if (t == 0) STAMP(5);
    asm volatile("bar.sync 3, 384;" ::: "memory");
    float wt[16];
    if (NPNN > 0) {
      #pragma unroll
      for (int i = 0; i < 4; i++)
        asm volatile("ld.shared.v4.f32 {%0,%1,%2,%3}, [%4];" : "=f"(wt[4 * i]), "=f"(wt[4 * i + 1]), "=f"(wt[4 * i + 2]), "=f"(wt[4 * i + 3]) : "r"(sb + OFF_WTS + (((w & 1) * 4 + i) * 32 + lane) * 16));
    }
    mbar_wait(sb + BAR_RECV + (c * 4 + w) * 8, 0);
    if (t == 0) STAMP(6);
    float s0a = 0.f, s0b = 0.f, s1a = 0.f, s1b = 0.f;
    #pragma unroll
    for (int j = 0; j < 8; j++) {
      uint32_t rv[4];
      asm volatile("ld.shared.v4.u32 {%0,%1,%2,%3}, [%4];" : "=r"(rv[0]), "=r"(rv[1]), "=r"(rv[2]), "=r"(rv[3]) : "r"(sb + OFF_RECV + j * 4096 + t * 16));
      #pragma unroll
      for (int m = 0; m < 2; m++) {
        float wa, wb;
        asm volatile("ld.shared.v2.f32 {%0,%1}, [%2];" : "=f"(wa), "=f"(wb) : "r"(sb + OFF_W2 + ((2 * j + m) * 8 + q * 2) * 4));
        #pragma unroll
        for (int e = 0; e < 4; e++) {
          const int a = 64 + 8 * j + 4 * m + e;
          const uint32_t pk = rv[2 * m + (e >> 1)];
          const float x = acc[a] + ((e & 1) ? bf_hi(pk) : bf_lo(pk));
          const float u = x * fmaf(x * x, 0.0356774081363001f, 0.7978845608028654f);
          float th; asm("tanh.approx.f32 %0, %1;" : "=f"(th) : "f"(u));
          const float aw = x * ((e & 1) ? wb : wa);
          if (e < 2) { s0a += aw; s0b = fmaf(aw, th, s0b); } else { s1a += aw; s1b = fmaf(aw, th, s1b); }
        }
      }
    }
    float s0 = s0a + s0b, s1 = s1a + s1b;
    s0 += __shfl_xor_sync(0xffffffffu, s0, 1); s1 += __shfl_xor_sync(0xffffffffu, s1, 1);
    s0 += __shfl_xor_sync(0xffffffffu, s0, 2); s1 += __shfl_xor_sync(0xffffffffu, s1, 2);
    if (t == 0) STAMP(7);
    const int me = nh * 2 + kh, owner = c * 2 + (w >> 1);
    const int rl = (w & 1) * 16 + g;
    if (owner == me) {
      if (q == 0) {
        asm volatile("st.shared.f32 [%0], %1;" :: "r"(sb + OFF_PART + rl * 4), "f"(s0) : "memory");
        asm volatile("st.shared.f32 [%0], %1;" :: "r"(sb + OFF_PART + (rl + 8) * 4), "f"(s1) : "memory");
      }
      asm volatile("bar.arrive 2, 96;" ::: "memory");
    } else if (q == 0) {
      unsigned long long* sl = g_slots + ((mt * 4 + owner) * 4 + me) * 32 + rl;
      asm volatile("st.relaxed.gpu.global.b64 [%0], %1;" :: "l"(sl), "l"((1ull << 32) | __float_as_uint(s0)) : "memory");
      asm volatile("st.relaxed.gpu.global.b64 [%0], %1;" :: "l"(sl + 8), "l"((1ull << 32) | __float_as_uint(s1)) : "memory");
    }
    if (NPNN > 0) {
      if (NSTAT == 8) pnn_triple(sb, wt, w, lane, 8 + c);
      else {
        #pragma unroll 1
        for (int p = NSTAT + c; p < NPAIR; p += 3) pnn_pair(sb, wt, w, lane, p);
      }
    }
    }
  } else if (warp >= 12) {
    asm volatile("bar.sync 0, 512;" ::: "memory");
    asm volatile("barrier.cluster.arrive.relaxed.aligned;" ::: "memory");
    asm volatile("setmaxnreg.dec.sync.aligned.u32 56;");
    const int lane = tid & 31;
    if (warp == 12) {
    auto load_stage = [&](int k) {
      const int s = k & 3;
      if (elect_one()) {
        mbar_expect_tx(sb + BAR_FULL + s * 8, STAGE);
        #pragma unroll
        for (int ww = 0; ww < 4; ww++)
          tma_w1(sb + s * STAGE + ww * 8192, &tmW, sb + BAR_FULL + s * 8, nh * 256 + ((ww ^ (kh ? 0 : 2)) << 6), f0 * 4 + k * 2);
      }
    };
    #pragma unroll
    for (int k = 0; k < NST; k++) load_stage(k);
    #pragma unroll 1
    for (int k = NST; k < 26; k++) {
      mbar_wait(sb + BAR_EMPTY + (k & 3) * 8, ((k >> 2) - 1) & 1);
      load_stage(k);
    }
      {
        const int me = nh * 2 + kh;
        float v = __bfloat162float(b2[0]);
        if (NHELP > 0 && lane >= OWN && NPNN > 0) {
          unsigned long long* hp = g_pnn + mt * 128 + me * 32 + lane;
          unsigned long long u; int it = 0;
          do { asm volatile("ld.relaxed.gpu.global.b64 %0, [%1];" : "=l"(u) : "l"(hp) : "memory"); if (++it > 4000000) __trap(); } while ((u >> 32) == 0);
          v += __uint_as_float((uint32_t)u);
          asm volatile("st.relaxed.gpu.global.b64 [%0], %1;" :: "l"(hp), "l"(0ull) : "memory");
        }
        __syncwarp();
        asm volatile("bar.sync 2, 96;" ::: "memory");
        { float pv; asm volatile("ld.shared.f32 %0, [%1];" : "=f"(pv) : "r"(sb + OFF_PART + lane * 4)); v += pv; }
        unsigned long long* sl = g_slots + ((mt * 4 + me) * 4) * 32 + lane;
        #pragma unroll
        for (int src = 0; src < 4; src++) {
          if (src == me) continue;
          unsigned long long u; int it = 0;
          do { asm volatile("ld.relaxed.gpu.global.b64 %0, [%1];" : "=l"(u) : "l"(sl + src * 32) : "memory"); if (++it > 4000000) __trap(); } while ((u >> 32) == 0);
          v += __uint_as_float((uint32_t)u);
          asm volatile("st.relaxed.gpu.global.b64 [%0], %1;" :: "l"(sl + src * 32), "l"(0ull) : "memory");
        }
        __syncwarp();
        if (NPNN > 0) {
          mbar_wait(sb + BAR_PALL, 0);
          float pa, pb; asm volatile("ld.shared.v2.f32 {%0, %1}, [%2];" : "=f"(pa), "=f"(pb) : "r"(sb + OFF_PART + 128 + lane * 8)); v += pa + pb;
        }
        out[mt * 128 + me * 32 + lane] = __float2bfloat16(v);
        if (lane == 0) { STAMP(9); GSTAMP(10); }
      }
    } else if (NPNN > 0) {
      mbar_wait(sb + BAR_IDX, 0);
      const uint32_t srow = sb + OFF_IDX + ((nh * 2 + kh) * 32) * kF * 4;
      const uint32_t half = lane >> 4, ch = lane & 15;
      const uint32_t o0 = (ch >> 3) * 8192 + half * 128, x0 = (ch & 7) ^ half;
      #pragma unroll 1
      for (int p = warp - 13; p < NPAIR; p += 3) {
        const uint32_t cell = pnn_cell(sb, p) + o0;
        const uint32_t gate = pnn_gate(p);
        mbar_wait(sb + gate, 0);
        {
          const uint32_t srw = srow + (2 * p * kF + half) * 4;
          uint32_t ids[26];
          #pragma unroll
          for (int i = 0; i < 26; i++) ids[i] = lds32(srw + (i / 13) * kF * 4 + (i % 13) * 8);
          #pragma unroll
          for (int i = 0; i < 26; i++)
            cp16(cell + (i / 13) * 4096 + (i % 13) * 256 + ((x0 ^ (((i % 13) & 3) * 2)) << 4), table + (size_t)(ids[i] * 16u + ch) * 16u);
        }
        asm volatile("cp.async.mbarrier.arrive.noinc.shared::cta.b64 [%0];" :: "r"(sb + BAR_PFULL + p * 8) : "memory");
      }
      asm volatile("cp.async.wait_all;" ::: "memory");
    }
    asm volatile("barrier.cluster.wait.aligned;" ::: "memory");
  } else {
    const int w = warp, lane = tid & 31, g = lane >> 2, q = lane & 3;
    asm volatile("bar.sync 0, 512;" ::: "memory");
    asm volatile("barrier.cluster.arrive.relaxed.aligned;" ::: "memory");
    asm volatile("setmaxnreg.dec.sync.aligned.u32 72;");
    asm volatile("st.shared.f32 [%0], %1;" :: "r"(sb + OFF_W2 + tid * 4), "f"(0.5f * __bfloat162float(w2[nh * 256 + kh * 128 + tid])) : "memory");
    float wt[16];
    pnn_load_weights(wt, w_p, w, lane);
    #pragma unroll
    for (int i = 0; i < 4; i++)
      if (w < 2) asm volatile("st.shared.v4.f32 [%0], {%1,%2,%3,%4};" :: "r"(sb + OFF_WTS + ((w * 4 + i) * 32 + lane) * 16), "f"(wt[4 * i]), "f"(wt[4 * i + 1]), "f"(wt[4 * i + 2]), "f"(wt[4 * i + 3]) : "memory");
    asm volatile("bar.arrive 3, 384;" ::: "memory");
    for (int i = tid; i < 2 * 2 * 6 * 8; i += 128) {
      const int cc = i & 7, r6 = (i >> 3) % 6, uh = i / 48;
      asm volatile("st.shared.v4.u32 [%0], {%1,%1,%1,%1};" :: "r"(sb + OFF_STAT + (uh & 1) * 8192 + ((uh >> 1) * 32 + kF + r6) * 128 + cc * 16), "r"(0u) : "memory");
    }
    asm volatile("bar.sync 1, 128;" ::: "memory");
    if (NPNN > 0) {
      #pragma unroll 1
      for (int p = 0; p < NSTAT - 1; p++) pnn_pair(sb, wt, w, lane, p);
      if (PNLATE) mbar_wait(sb + BAR_FREE01, 0);
      #pragma unroll 1
      for (int p = NSTAT - 1; p < NPAIR; p += 3) pnn_pair(sb, wt, w, lane, p);
    }
    if (tid == 0) STAMP(8);
    asm volatile("barrier.cluster.wait.aligned;" ::: "memory");
  }
}

typedef CUresult (*EncodeFn)(CUtensorMap*, CUtensorMapDataType, cuuint32_t, void*, const cuuint64_t*, const cuuint64_t*, const cuuint32_t*,
                             const cuuint32_t*, CUtensorMapInterleave, CUtensorMapSwizzle, CUtensorMapL2promotion, CUtensorMapFloatOOBfill);
}

extern "C" void kernel_launch(void* const* d_in, const int* in_sizes, int n_in, void* d_out, int out_size) {
  (void)in_sizes; (void)n_in; (void)out_size;
  static EncodeFn enc = nullptr;
  if (!enc) {
    void* fn = nullptr; cudaDriverEntryPointQueryResult qr;
    cudaGetDriverEntryPoint("cuTensorMapEncodeTiled", &fn, cudaEnableDefault, &qr);
    enc = (EncodeFn)fn;
    cudaFuncSetAttribute(pnn_mlp_kernel, cudaFuncAttributeMaxDynamicSharedMemorySize, SMEM_BYTES);
  }
  CUtensorMap tm;
  cuuint64_t dims[5] = {512, 2, 4, 4, 104};
  cuuint64_t strides[4] = {1024, 8 * 1024, 2 * 1024, 32 * 1024};
  cuuint32_t box[5] = {64, 2, 4, 4, 2};
  cuuint32_t es[5] = {1, 1, 1, 1, 1};
  enc(&tm, CU_TENSOR_MAP_DATA_TYPE_BFLOAT16, 5, d_in[3], dims, strides, box, es, CU_TENSOR_MAP_INTERLEAVE_NONE, CU_TENSOR_MAP_SWIZZLE_128B,
      CU_TENSOR_MAP_L2_PROMOTION_L2_128B, CU_TENSOR_MAP_FLOAT_OOB_FILL_NONE);
  cudaLaunchConfig_t cfg = {};
  cfg.gridDim = dim3(128 + NHELP); cfg.blockDim = dim3(512); cfg.dynamicSmemBytes = SMEM_BYTES; cfg.stream = cudaStreamPerThread;
  cudaLaunchAttribute at[1];
  at[0].id = cudaLaunchAttributeClusterDimension; at[0].val.clusterDim.x = 2; at[0].val.clusterDim.y = 1; at[0].val.clusterDim.z = 1;
  cfg.attrs = at; cfg.numAttrs = 1;
  cudaLaunchKernelEx(&cfg, pnn_mlp_kernel, tm, (const int*)d_in[0], (const char*)d_in[1], (const __nv_bfloat16*)d_in[2],
                     (const __nv_bfloat16*)d_in[4], (const __nv_bfloat16*)d_in[5], (const __nv_bfloat16*)d_in[6], (__nv_bfloat16*)d_out, 0u);
}
```

```cpp
#include <cuda_runtime.h>
#include <cuda_bf16.h>
#include <cuda.h>
#include <stdint.h>

#define NPNN 8
#define PFD 0
#define PF0 0
#define PNGO 3
#define NSTAT_V (NHELP_V ? 5 : 8)
#define PNLATE 1
#define PNR 2
#define PNDELAY 1
#define PNPF 1
namespace {

constexpr int kB = 4096, kF = 26, kD = 128, kH = 512;
constexpr int NST = 4;
constexpr uint32_t STAGE = 32768;
constexpr uint32_t PCELL = 16384;
constexpr uint32_t OFF_RECV = NST * STAGE;
constexpr uint32_t OFF_STAT = OFF_RECV + 32768;
constexpr uint32_t OFF_IDX  = OFF_STAT + PCELL;
constexpr uint32_t OFF_WTS  = OFF_IDX + 128 * kF * 4;
constexpr uint32_t OFF_W2   = OFF_WTS + 4096;
constexpr uint32_t OFF_PART = OFF_W2 + 512;
constexpr uint32_t OFF_TRC  = OFF_PART + 384;
constexpr uint32_t OFF_BAR  = OFF_TRC + 112;
constexpr uint32_t SMEM_USED = OFF_BAR + 58 * 8;
static_assert(SMEM_USED <= 199680, "keep the 196 KB carve-out (60 KB of L1)");
constexpr uint32_t SMEM_BYTES = SMEM_USED;
constexpr uint32_t BAR_FULL = OFF_BAR, BAR_EMPTY = OFF_BAR + 32, BAR_IDX = OFF_BAR + 64, BAR_RECV = OFF_BAR + 72;
constexpr uint32_t BAR_GO = OFF_BAR + 136, BAR_FREE2 = OFF_BAR + 144, BAR_FREE3 = OFF_BAR + 152, BAR_FREE01 = OFF_BAR + 160;
constexpr uint32_t BAR_PFULL = OFF_BAR + 168, BAR_PDONE = BAR_PFULL + 16 * 8, BAR_PALL = BAR_PDONE + 16 * 8, BAR_FREES = BAR_PALL + 8, OFF_QUEUE = BAR_FREES + 8;
#define NHELP_V 4
constexpr int NHELP = NHELP_V;
constexpr int OWN = NHELP ? 26 : 32, NPAIR = OWN / 2;
constexpr int NEXT = NHELP ? 32 - OWN : 1;

__device__ unsigned long long g_slots[32 * 4 * 4 * 32];
__device__ unsigned long long g_pnn[4096];
#define STAMP(i)
#define GSTAMP(i)

__device__ __forceinline__ void wgmma_n128_lo(float (&d)[128], uint32_t a0, uint32_t a1, uint32_t a2, uint32_t a3, uint32_t dlo) {
  asm volatile("{\n.reg .b64 db;\nmov.b64 db, {%68, 0x40000040};\n"
    "wgmma.mma_async.sync.aligned.m64n128k16.f32.bf16.bf16 "
    "{%0, %1, %2, %3, %4, %5, %6, %7, %8, %9, %10, %11, %12, %13, %14, %15, %16, %17, %18, %19, %20, %21, %22, %23, %24, %25, %26, %27, %28, %29, %30, %31, %32, %33, %34, %35, %36, %37, %38, %39, %40, %41, %42, %43, %44, %45, %46, %47, %48, %49, %50, %51, %52, %53, %54, %55, %56, %57, %58, %59, %60, %61, %62, %63}, "
    "{%64, %65, %66, %67}, db, 1, 1, 1, 1;\n}\n"
    : "+f"(d[0]), "+f"(d[1]), "+f"(d[2]), "+f"(d[3]), "+f"(d[4]), "+f"(d[5]), "+f"(d[6]), "+f"(d[7]), "+f"(d[8]), "+f"(d[9]), "+f"(d[10]), "+f"(d[11]), "+f"(d[12]), "+f"(d[13]), "+f"(d[14]), "+f"(d[15]), "+f"(d[16]), "+f"(d[17]), "+f"(d[18]), "+f"(d[19]), "+f"(d[20]), "+f"(d[21]), "+f"(d[22]), "+f"(d[23]), "+f"(d[24]), "+f"(d[25]), "+f"(d[26]), "+f"(d[27]), "+f"(d[28]), "+f"(d[29]), "+f"(d[30]), "+f"(d[31]), "+f"(d[32]), "+f"(d[33]), "+f"(d[34]), "+f"(d[35]), "+f"(d[36]), "+f"(d[37]), "+f"(d[38]), "+f"(d[39]), "+f"(d[40]), "+f"(d[41]), "+f"(d[42]), "+f"(d[43]), "+f"(d[44]), "+f"(d[45]), "+f"(d[46]), "+f"(d[47]), "+f"(d[48]), "+f"(d[49]), "+f"(d[50]), "+f"(d[51]), "+f"(d[52]), "+f"(d[53]), "+f"(d[54]), "+f"(d[55]), "+f"(d[56]), "+f"(d[57]), "+f"(d[58]), "+f"(d[59]), "+f"(d[60]), "+f"(d[61]), "+f"(d[62]), "+f"(d[63])
    : "r"(a0), "r"(a1), "r"(a2), "r"(a3), "r"(dlo));
}
__device__ __forceinline__ void wgmma_n128_hi(float (&d)[128], uint32_t a0, uint32_t a1, uint32_t a2, uint32_t a3, uint32_t dlo) {
  asm volatile("{\n.reg .b64 db;\nmov.b64 db, {%68, 0x40000040};\n"
    "wgmma.mma_async.sync.aligned.m64n128k16.f32.bf16.bf16 "
    "{%0, %1, %2, %3, %4, %5, %6, %7, %8, %9, %10, %11, %12, %13, %14, %15, %16, %17, %18, %19, %20, %21, %22, %23, %24, %25, %26, %27, %28, %29, %30, %31, %32, %33, %34, %35, %36, %37, %38, %39, %40, %41, %42, %43, %44, %45, %46, %47, %48, %49, %50, %51, %52, %53, %54, %55, %56, %57, %58, %59, %60, %61, %62, %63}, "
    "{%64, %65, %66, %67}, db, 1, 1, 1, 1;\n}\n"
    : "+f"(d[64]), "+f"(d[65]), "+f"(d[66]), "+f"(d[67]), "+f"(d[68]), "+f"(d[69]), "+f"(d[70]), "+f"(d[71]), "+f"(d[72]), "+f"(d[73]), "+f"(d[74]), "+f"(d[75]), "+f"(d[76]), "+f"(d[77]), "+f"(d[78]), "+f"(d[79]), "+f"(d[80]), "+f"(d[81]), "+f"(d[82]), "+f"(d[83]), "+f"(d[84]), "+f"(d[85]), "+f"(d[86]), "+f"(d[87]), "+f"(d[88]), "+f"(d[89]), "+f"(d[90]), "+f"(d[91]), "+f"(d[92]), "+f"(d[93]), "+f"(d[94]), "+f"(d[95]), "+f"(d[96]), "+f"(d[97]), "+f"(d[98]), "+f"(d[99]), "+f"(d[100]), "+f"(d[101]), "+f"(d[102]), "+f"(d[103]), "+f"(d[104]), "+f"(d[105]), "+f"(d[106]), "+f"(d[107]), "+f"(d[108]), "+f"(d[109]), "+f"(d[110]), "+f"(d[111]), "+f"(d[112]), "+f"(d[113]), "+f"(d[114]), "+f"(d[115]), "+f"(d[116]), "+f"(d[117]), "+f"(d[118]), "+f"(d[119]), "+f"(d[120]), "+f"(d[121]), "+f"(d[122]), "+f"(d[123]), "+f"(d[124]), "+f"(d[125]), "+f"(d[126]), "+f"(d[127])
    : "r"(a0), "r"(a1), "r"(a2), "r"(a3), "r"(dlo));
}

__device__ __forceinline__ uint32_t smem_u32(const void* p) { return (uint32_t)__cvta_generic_to_shared(p); }
__device__ __forceinline__ void mbar_init(uint32_t bar, uint32_t cnt) { asm volatile("mbarrier.init.shared::cta.b64 [%0], %1;" :: "r"(bar), "r"(cnt)); }
__device__ __forceinline__ void mbar_expect_tx(uint32_t bar, uint32_t bytes) { asm volatile("mbarrier.arrive.expect_tx.shared::cta.b64 _, [%0], %1;" :: "r"(bar), "r"(bytes) : "memory"); }
__device__ __forceinline__ void mbar_arrive(uint32_t bar) { asm volatile("mbarrier.arrive.shared::cta.b64 _, [%0];" :: "r"(bar) : "memory"); }
__device__ __forceinline__ void mbar_wait(uint32_t bar, uint32_t parity) {
  asm volatile("{\n.reg .pred p;\n.reg .u32 c;\nmov.u32 c, 0;\n"
    "LAB_WAIT:\nmbarrier.try_wait.parity.shared::cta.b64 p, [%0], %1;\n@p bra.uni LAB_DONE;\n"
    "add.u32 c, c, 1;\nsetp.lt.u32 p, c, 4000000;\n@p bra.uni LAB_WAIT;\ntrap;\nLAB_DONE:\n}" :: "r"(bar), "r"(parity) : "memory");
}
__device__ __forceinline__ uint32_t desc_lo(uint32_t addr) { return ((addr & 0x3FFFF) >> 4) | ((8192u >> 4) << 16); }
__device__ __forceinline__ uint4 ldg128(const void* p) {
  uint4 v;
  asm volatile("ld.global.nc.L1::no_allocate.v4.u32 {%0,%1,%2,%3}, [%4];" : "=r"(v.x), "=r"(v.y), "=r"(v.z), "=r"(v.w) : "l"(p));
  return v;
}
__device__ __forceinline__ uint4 ldg128_row(const void* p) {
  uint4 v;
  asm volatile("ld.global.nc.L1::no_allocate.L2::256B.v4.u32 {%0,%1,%2,%3}, [%4];" : "=r"(v.x), "=r"(v.y), "=r"(v.z), "=r"(v.w) : "l"(p));
  return v;
}
__device__ __forceinline__ uint32_t lds32(uint32_t a) { uint32_t v; asm volatile("ld.shared.u32 %0, [%1];" : "=r"(v) : "r"(a)); return v; }
__device__ __forceinline__ void tma_w1(uint32_t dst, const CUtensorMap* tm, uint32_t bar, int x, int kb) {
  asm volatile("cp.async.bulk.tensor.5d.shared::cluster.global.mbarrier::complete_tx::bytes [%0], [%1, {%3, %4, %4, %4, %5}], [%2];"
    :: "r"(dst), "l"(tm), "r"(bar), "r"(x), "r"(0), "r"(kb) : "memory");
}
__device__ __forceinline__ float bf_lo(uint32_t v) { return __uint_as_float(v << 16); }
__device__ __forceinline__ float bf_hi(uint32_t v) { return __uint_as_float(v & 0xffff0000u); }
__device__ __forceinline__ uint32_t pack_bf16(float lo, float hi) { uint32_t r; asm("cvt.rn.bf16x2.f32 %0, %1, %2;" : "=r"(r) : "f"(hi), "f"(lo)); return r; }
__device__ __forceinline__ void mma16816(float (&d)[4], uint32_t a0, uint32_t a1, uint32_t a2, uint32_t a3, uint32_t b0, uint32_t b1) {
  asm volatile("mma.sync.aligned.m16n8k16.row.col.f32.bf16.bf16.f32 {%0,%1,%2,%3}, {%4,%5,%6,%7}, {%8,%9}, {%0,%1,%2,%3};"
    : "+f"(d[0]), "+f"(d[1]), "+f"(d[2]), "+f"(d[3]) : "r"(a0), "r"(a1), "r"(a2), "r"(a3), "r"(b0), "r"(b1));
}

__device__ __forceinline__ uint32_t rd_tid() { uint32_t v; asm volatile("mov.u32 %0, %tid.x;" : "=r"(v)); return v; }
__device__ __forceinline__ uint32_t rd_cta() { uint32_t v; asm volatile("mov.u32 %0, %ctaid.x;" : "=r"(v)); return v; }
template <int LO, int HI> __device__ __forceinline__ void fence_acc(float (&d)[128]) {
  #pragma unroll
  for (int i = LO; i < HI; i++) asm volatile("" : "+f"(d[i]) :: "memory");
}
__device__ __forceinline__ bool elect_one() {
  uint32_t p; asm volatile("{\n.reg .pred P;\nelect.sync _|P, 0xffffffff;\nselp.u32 %0, 1, 0, P;\n}" : "=r"(p)); return p != 0;
}
constexpr int NSTAT = NSTAT_V;
constexpr int NREUSE = NPAIR - NSTAT - 8;
static_assert(NREUSE == 0 || NREUSE == 2, "tail schedule");
__device__ __forceinline__ void cp16(uint32_t dst, const void* src) { asm volatile("cp.async.cg.shared.global [%0], [%1], 16;" :: "r"(dst), "l"(src) : "memory"); }
__device__ __forceinline__ uint32_t pnn_cell(uint32_t sb, int p) {
  if (p < NSTAT) return sb + OFF_STAT;
  p = (p - NSTAT) & 7;
  return p < 4 ? sb + (p + 4) * PCELL : sb + (p & 1) * 2 * PCELL + (p >= 6 ? PCELL : 0);
}
__device__ __forceinline__ uint32_t pnn_gate(int p) {
  if (p == 0) return BAR_GO;
  if (p < NSTAT) return BAR_PDONE + (p - 1) * 8;
  const int j = p - NSTAT;
  return j < 2 ? BAR_FREE2 : (j < 4 ? BAR_FREE3 : (j < 6 ? BAR_FREES : (j < 8 ? BAR_FREE01 : BAR_PDONE + (p - 8) * 8)));
}
__device__ __forceinline__ void pnn_stage(uint32_t sb, const char* __restrict__ table, int row0, int lane, int p) {
  const uint32_t half = lane >> 4, ch = lane & 15;
  const uint32_t cell = pnn_cell(sb, p) + (ch >> 3) * 8192 + half * 128, x0 = (ch & 7) ^ half;
  const uint32_t srw = sb + OFF_IDX + ((row0 + 2 * p) * kF + half) * 4;
  mbar_wait(sb + pnn_gate(p), 0);
  uint32_t ids[26];
  #pragma unroll
  for (int i = 0; i < 26; i++) ids[i] = lds32(srw + (i / 13) * kF * 4 + (i % 13) * 8);
  #pragma unroll
  for (int i = 0; i < 26; i++)
    cp16(cell + (i / 13) * 4096 + (i % 13) * 256 + ((x0 ^ (((i % 13) & 3) * 2)) << 4), table + (size_t)(ids[i] * 16u + ch) * 16u);
  asm volatile("cp.async.mbarrier.arrive.noinc.shared::cta.b64 [%0];" :: "r"(sb + BAR_PFULL + p * 8) : "memory");
}
__device__ __forceinline__ void wgmma_gram(float (&d)[32], uint32_t dlo, int acc) {
  asm volatile("{\n.reg .pred p;\n.reg .b64 db;\nsetp.ne.b32 p, %33, 0;\nmov.b64 db, {%32, 0x40000040};\n"
    "wgmma.mma_async.sync.aligned.m64n64k16.f32.bf16.bf16 "
    "{%0,%1,%2,%3,%4,%5,%6,%7,%8,%9,%10,%11,%12,%13,%14,%15,%16,%17,%18,%19,%20,%21,%22,%23,%24,%25,%26,%27,%28,%29,%30,%31}, db, db, p, 1, 1, 0, 0;\n}\n"
    : "+f"(d[0]), "+f"(d[1]), "+f"(d[2]), "+f"(d[3]), "+f"(d[4]), "+f"(d[5]), "+f"(d[6]), "+f"(d[7]),
      "+f"(d[8]), "+f"(d[9]), "+f"(d[10]), "+f"(d[11]), "+f"(d[12]), "+f"(d[13]), "+f"(d[14]), "+f"(d[15]),
      "+f"(d[16]), "+f"(d[17]), "+f"(d[18]), "+f"(d[19]), "+f"(d[20]), "+f"(d[21]), "+f"(d[22]), "+f"(d[23]),
      "+f"(d[24]), "+f"(d[25]), "+f"(d[26]), "+f"(d[27]), "+f"(d[28]), "+f"(d[29]), "+f"(d[30]), "+f"(d[31])
    : "r"(dlo), "r"(acc));
}

__device__ __forceinline__ void pnn_issue(float (&D)[32], uint32_t sb, int p) {
  mbar_wait(sb + BAR_PFULL + p * 8, 0);
  asm volatile("fence.proxy.async.shared::cta;" ::: "memory");
  const uint32_t dl = ((pnn_cell(sb, p) & 0x3FFFF) >> 4) | (1u << 16);
  asm volatile("wgmma.fence.sync.aligned;" ::: "memory");
  #pragma unroll
  for (int kk = 0; kk < 8; kk++) wgmma_gram(D, dl + (((kk >> 2) * 8192 + (kk & 3) * 32) >> 4), kk > 0);
  asm volatile("wgmma.commit_group.sync.aligned;" ::: "memory");
}
__device__ __forceinline__ float pnn_dot(float (&D)[32], const float (&wt)[16], int w, int lane) {
  const bool pc = (lane & 3) == 0, pr = !(w & 1) || lane < 8;
  #pragma unroll
  for (int i = 0; i < 32; i++) asm volatile("" : "+f"(D[i]) :: "memory");
  float s4[4] = {0.f, 0.f, 0.f, 0.f};
  if (w >> 1) {
    #pragma unroll
    for (int i = 0; i < 16; i++) { const bool ok = ((i >> 2) < 3 || pc) && ((i & 2) == 0 || pr); if (ok) s4[i & 3] = fmaf(D[16 + i], wt[i], s4[i & 3]); }
  } else {
    #pragma unroll
    for (int i = 0; i < 16; i++) { const bool ok = ((i >> 2) < 3 || pc) && ((i & 2) == 0 || pr); if (ok) s4[i & 3] = fmaf(D[i], wt[i], s4[i & 3]); }
  }
  return (s4[0] + s4[1]) + (s4[2] + s4[3]);
}
__device__ __forceinline__ void pnn_store(uint32_t sb, float sum, int w, int lane, int p) {
  if (lane == 0) {
    asm volatile("st.shared.f32 [%0], %1;" :: "r"(sb + OFF_PART + 128 + ((2 * p + (w >> 1)) * 2 + (w & 1)) * 4), "f"(sum) : "memory");
    mbar_arrive(sb + BAR_PALL);
  }
}
__device__ __forceinline__ void pnn_pair(uint32_t sb, const float (&wt)[16], int w, int lane, int p) {
  float D[32];
  pnn_issue(D, sb, p);
  asm volatile("wgmma.wait_group.sync.aligned 0;" ::: "memory");
  if (w == 0 && lane == 0) mbar_arrive(sb + BAR_PDONE + p * 8);
  float sum = pnn_dot(D, wt, w, lane);
  #pragma unroll
  for (int o = 16; o > 0; o >>= 1) sum += __shfl_xor_sync(0xffffffffu, sum, o);
  pnn_store(sb, sum, w, lane, p);
}
template <int ST>
__device__ __forceinline__ void pnn_triple_t(uint32_t sb, const float (&wt)[16], int w, int lane, int p) {
  float D0[32], D1[32], D2[32];
  pnn_issue(D0, sb, p); pnn_issue(D1, sb, p + ST); pnn_issue(D2, sb, p + 2 * ST);
  asm volatile("wgmma.wait_group.sync.aligned 2;" ::: "memory");
  float a = pnn_dot(D0, wt, w, lane);
  asm volatile("wgmma.wait_group.sync.aligned 1;" ::: "memory");
  float b = pnn_dot(D1, wt, w, lane);
  asm volatile("wgmma.wait_group.sync.aligned 0;" ::: "memory");
  float c = pnn_dot(D2, wt, w, lane);
  #pragma unroll
  for (int o = 16; o > 0; o >>= 1) { a += __shfl_xor_sync(0xffffffffu, a, o); b += __shfl_xor_sync(0xffffffffu, b, o); c += __shfl_xor_sync(0xffffffffu, c, o); }
  pnn_store(sb, a, w, lane, p); pnn_store(sb, b, w, lane, p + ST); pnn_store(sb, c, w, lane, p + 2 * ST);
}
__device__ __forceinline__ void pnn_triple(uint32_t sb, const float (&wt)[16], int w, int lane, int p) { pnn_triple_t<3>(sb, wt, w, lane, p); }
__device__ __forceinline__ void pnn_triple2(uint32_t sb, const float (&wt)[16], int w, int lane, int p) { pnn_triple_t<2>(sb, wt, w, lane, p); }
__device__ __forceinline__ void pnn_load_weights(float (&wt)[16], const __nv_bfloat16* __restrict__ w_p, int w, int lane) {
  #pragma unroll
  for (int i = 0; i < 16; i++) {
    const int fi = (w & 1) * 16 + (lane >> 2) + 8 * ((i >> 1) & 1), fj = 8 * (i >> 2) + 2 * (lane & 3) + (i & 1);
    wt[i] = (fi < kF && fj < kF) ? __bfloat162float(w_p[fi * kF + fj]) : 0.f;
  }
}

constexpr uint32_t HCELL = kF * 256, HOFF_WTS = 28 * HCELL, HOFF_ZERO = HOFF_WTS + 3072;
__device__ __forceinline__ float helper_gram(uint32_t sb, int lane, uint32_t cell) {
  const uint32_t lrow = (lane & 7) + ((lane >> 3) & 1) * 8, lch = lane >> 4;
  float G[6][4];
  #pragma unroll
  for (int b = 0; b < 6; b++) { G[b][0] = G[b][1] = G[b][2] = G[b][3] = 0.f; }
  #pragma unroll
  for (int s = 0; s < 8; s++) {
    const uint32_t ch = 2 * s + lch;
    const uint32_t o = lrow * 256 + (ch >> 3) * 128 + (((ch & 7) ^ (lrow & 7)) << 4);
    uint32_t p0, p1, p2, p3, c0, c1, c2, c3;
    asm volatile("ldmatrix.sync.aligned.m8n8.x4.shared.b16 {%0,%1,%2,%3}, [%4];" : "=r"(p0), "=r"(p1), "=r"(p2), "=r"(p3) : "r"(cell + o));
    asm volatile("ldmatrix.sync.aligned.m8n8.x4.shared.b16 {%0,%1,%2,%3}, [%4];" : "=r"(c0), "=r"(c1), "=r"(c2), "=r"(c3)
                 : "r"(lrow < 10 ? cell + 4096 + o : sb + HOFF_ZERO));
    mma16816(G[0], p0, p1, p2, p3, p0, p2);
    mma16816(G[4], c0, c1, c2, c3, c0, c2);
    mma16816(G[1], p0, p1, p2, p3, p1, p3);
    mma16816(G[5], c0, c1, c2, c3, c1, c3);
    mma16816(G[2], p0, p1, p2, p3, c0, c2);
    mma16816(G[3], p0, p1, p2, p3, c1, c3);
  }
  float s0 = 0.f, s1 = 0.f;
  #pragma unroll
  for (int b = 0; b < 6; b++) {
    float4 wv;
    asm volatile("ld.shared.v4.f32 {%0,%1,%2,%3}, [%4];" : "=f"(wv.x), "=f"(wv.y), "=f"(wv.z), "=f"(wv.w) : "r"(sb + HOFF_WTS + (b * 32 + lane) * 16));
    s0 = fmaf(G[b][0], wv.x, s0); s1 = fmaf(G[b][1], wv.y, s1); s0 = fmaf(G[b][2], wv.z, s0); s1 = fmaf(G[b][3], wv.w, s1);
  }
  float sum = s0 + s1;
  #pragma unroll
  for (int o = 16; o > 0; o >>= 1) sum += __shfl_xor_sync(0xffffffffu, sum, o);
  return sum;
}

struct Half { uint4 x, y; };

__global__ void __cluster_dims__(2, 1, 1) __launch_bounds__(512, 1)
pnn_mlp_kernel(const __grid_constant__ CUtensorMap tmW, const int* __restrict__ idx, const char* __restrict__ table,
               const __nv_bfloat16* __restrict__ w_p, const __nv_bfloat16* __restrict__ b1, const __nv_bfloat16* __restrict__ w2,
               const __nv_bfloat16* __restrict__ b2, __nv_bfloat16* __restrict__ out, const void* __restrict__ w1g, uint32_t zero) {
  extern __shared__ __align__(1024) uint8_t smem_raw[];
  const uint32_t sb = smem_u32(smem_raw);
  if (sb & 1023u) __trap();
  const int tid = threadIdx.x;
  const int warp = __shfl_sync(0xffffffffu, tid >> 5, 0);
  if (NHELP > 0 && blockIdx.x < NHELP) {
    constexpr int HW = 14, NS = 32 * NEXT;
    static_assert(HOFF_ZERO + 16 <= SMEM_BYTES, "helper smem layout");
    const int lane = tid & 31;
    auto sample_of = [&](int j) { return (blockIdx.x * 32 + j / NEXT) * 32 + OWN + j % NEXT; };
    auto ld_ids = [&](int j) { return (lane < kF && j < NS) ? __ldg(idx + (size_t)sample_of(j) * kF + lane) : 0; };
    int id0 = ld_ids(warp), id1 = ld_ids(warp + HW), id2 = ld_ids(warp + 2 * HW);
    for (int e = tid; e < 6 * 128; e += 512) {
      const int b = e >> 7, e2 = e & 3, ln = (e >> 2) & 31;
      const int fi = (b < 4 ? 0 : 16) + (e2 >> 1) * 8 + (ln >> 2), fj = (b < 4 ? b : b - 2) * 8 + (ln & 3) * 2 + (e2 & 1);
      float v = 0.f;
      if (fi < kF && fj < kF) {
        v = __bfloat162float(w_p[fi * kF + fj]);
        if (b == 2 || b == 3) v += __bfloat162float(w_p[fj * kF + fi]);
      }
      asm volatile("st.shared.f32 [%0], %1;" :: "r"(sb + HOFF_WTS + e * 4), "f"(v) : "memory");
    }
    if (tid < 4) asm volatile("st.shared.u32 [%0], %1;" :: "r"(sb + HOFF_ZERO + tid * 4), "r"(0u) : "memory");
    __syncthreads();
    if (warp < HW) {
      const uint32_t cbase = sb + warp * 2 * HCELL;
      const uint32_t half = lane >> 4, ch = lane & 15;
      const uint32_t o0 = half * 256 + (ch >> 3) * 128, x0 = (ch & 7) ^ half;
      auto stage = [&](int myid, uint32_t cell) {
        #pragma unroll
        for (int i = 0; i < 13; i++) {
          const uint32_t id = __shfl_sync(0xffffffffu, myid, 2 * i + half);
          cp16(cell + o0 + i * 512 + ((x0 ^ ((i & 3) * 2)) << 4), table + (size_t)(id * 16u + ch) * 16u);
        }
        asm volatile("cp.async.commit_group;" ::: "memory");
      };
      stage(id0, cbase);
      int buf = 0;
      #pragma unroll 1
      for (int j = warp; j < NS; j += HW) {
        if (j + HW < NS) stage(id1, cbase + (buf ^ 1) * HCELL); else asm volatile("cp.async.commit_group;" ::: "memory");
        id1 = id2; id2 = ld_ids(j + 3 * HW);
        asm volatile("cp.async.wait_group 1;" ::: "memory");
        __syncwarp();
        const float sum = helper_gram(sb, lane, cbase + buf * HCELL);
        if (lane == 0) asm volatile("st.relaxed.gpu.global.b64 [%0], %1;" :: "l"(g_pnn + sample_of(j)), "l"((1ull << 32) | __float_as_uint(sum)) : "memory");
        __syncwarp();
        buf ^= 1;
      }
    }
    return;
  }
  const int bid = blockIdx.x - NHELP;
  const int kh = bid & 1, pair = bid >> 1, nh = pair & 1, mt = pair >> 1;
  const int f0 = kh * 13;

  if (warp == 13) {
    const int l = tid & 31;
    const char* pg = l < 13 ? table + (size_t)l * (2u << 20) : (const char*)w1g + (size_t)((l - 13) & 1) * (2u << 20);
    if (l < 15) asm volatile("prefetch.global.L2 [%0];" :: "l"(pg));
  }
  if (tid == 32) asm volatile("prefetch.tensormap [%0];" :: "l"(&tmW) : "memory");
  if (tid == 0) {
    STAMP(0); GSTAMP(1);
    mbar_init(sb + BAR_IDX, 1);
    #pragma unroll
    for (int s = 0; s < NST; s++) { mbar_init(sb + BAR_FULL + s * 8, 1); mbar_init(sb + BAR_EMPTY + s * 8, 2); }
    #pragma unroll
    for (int w = 0; w < 8; w++) mbar_init(sb + BAR_RECV + w * 8, 1);
    #pragma unroll
    for (int p = 0; p < NPAIR; p++) mbar_init(sb + BAR_PFULL + p * 8, 32);
    #pragma unroll
    for (int p = 0; p < 16; p++) mbar_init(sb + BAR_PDONE + p * 8, 1);
    mbar_init(sb + BAR_PALL, 4 * NPAIR); mbar_init(sb + BAR_FREES, 2);
    asm volatile("st.shared.u32 [%0], %1;" :: "r"(sb + OFF_QUEUE), "r"(0u) : "memory");
    mbar_init(sb + BAR_GO, 1); mbar_init(sb + BAR_FREE2, 2); mbar_init(sb + BAR_FREE3, 2); mbar_init(sb + BAR_FREE01, 2);
    asm volatile("fence.mbarrier_init.release.cluster;" ::: "memory");
    mbar_expect_tx(sb + BAR_IDX, 128 * kF * 4);
    asm volatile("cp.async.bulk.shared::cluster.global.mbarrier::complete_tx::bytes [%0], [%1], %2, [%3];"
      :: "r"(sb + OFF_IDX), "l"(idx + (size_t)mt * 128 * kF), "r"(128 * kF * 4), "r"(sb + BAR_IDX) : "memory");
#define EARLYW1 1
    #pragma unroll
    for (int k = 0; k < EARLYW1; k++) {
      mbar_expect_tx(sb + BAR_FULL + k * 8, STAGE);
      #pragma unroll
      for (int ww = 0; ww < 4; ww++)
        tma_w1(sb + k * STAGE + ww * 8192, &tmW, sb + BAR_FULL + k * 8, nh * 256 + ((ww ^ (kh ? 0 : 2)) << 6), f0 * 4 + k * 2);
    }
  }

  if (warp >= 4 && warp < 12) {
    const int t = tid - 128, c = (warp - 4) >> 2, w = warp & 3, lane = tid & 31, g = lane >> 2, q = lane & 3;
    const int r0 = c * 64 + w * 16 + g;
    const int* ip = idx + (size_t)(mt * 128 + r0) * kF + f0;
    const uint32_t i00 = __ldg(ip), i10 = __ldg(ip + 8 * kF), i01 = __ldg(ip + 1), i11 = __ldg(ip + 8 * kF + 1);
    uint32_t braw[16];
    {
      const uint32_t* bp = reinterpret_cast<const uint32_t*>(b1 + nh * 256 + kh * 128) + q;
      #pragma unroll
      for (int i = 0; i < 16; i++) braw[i] = __ldg(bp + i * 4);
    }
    asm volatile("bar.sync 0, 512;" ::: "memory");
    if (t == 0) STAMP(11);
    asm volatile("barrier.cluster.arrive.relaxed.aligned;" ::: "memory");
    asm volatile("setmaxnreg.inc.sync.aligned.u32 192;");
    if (t == 0) STAMP(12);
    if (t == 0) STAMP(13);
    if (elect_one()) mbar_expect_tx(sb + BAR_RECV + (c * 4 + w) * 8, 4096);

    Half R[4];
    const char *p0, *p1;
    auto setptr = [&](uint32_t i0, uint32_t i1) {
      const uint32_t qq = rd_tid() & 3;
      p0 = table + (size_t)(i0 * 16u + qq) * 16u; p1 = table + (size_t)(i1 * 16u + qq) * 16u;
    };
#define ROWHINT 2
    auto refill = [&](Half& h, int quarter) {
      if (ROWHINT == 2 || (ROWHINT == 1 && quarter == 0)) { h.x = ldg128_row(p0 + quarter * 64); h.y = ldg128_row(p1 + quarter * 64); }
      else { h.x = ldg128(p0 + quarter * 64); h.y = ldg128(p1 + quarter * 64); }
    };
    setptr(i00, i10);
    refill(R[0], 0); refill(R[1], 1); refill(R[2], 2); refill(R[3], 3);
    if (t == 0) STAMP(14);
    setptr(i01, i11);

    float acc[128];
    #pragma unroll
    for (int i = 0; i < 64; i++) acc[i] = 0.f;
    #pragma unroll
    for (int i = 0; i < 16; i++) {
      acc[64 + 4 * i + 0] = bf_lo(braw[i]); acc[64 + 4 * i + 1] = bf_hi(braw[i]);
      acc[64 + 4 * i + 2] = bf_lo(braw[i]); acc[64 + 4 * i + 3] = bf_hi(braw[i]);
    }
    fence_acc<0, 128>(acc);
    if (t == 0) STAMP(15);
    const uint32_t sidx0 = sb + OFF_IDX + (r0 * kF + f0) * 4;
    mbar_wait(sb + BAR_IDX, 0);
    if (t == 0) STAMP(2);

#define FRAG(h, u, v) uint32_t f0_ = h.x.u ^ zero, f1_ = h.y.u ^ zero, f2_ = h.x.v ^ zero, f3_ = h.y.v ^ zero
#define WG_FENCE()  asm volatile("wgmma.fence.sync.aligned;" ::: "memory")
#define WG_COMMIT() asm volatile("wgmma.commit_group.sync.aligned;" ::: "memory")
#define WG_WAIT(n)  asm volatile("wgmma.wait_group.sync.aligned " #n ";" ::: "memory")
#define XORZ(d, s)  asm volatile("xor.b32 %0, %1, %2;" : "=r"(d) : "r"(s), "r"(zero))
    const uint32_t dbase = desc_lo(sb);
    auto mma256 = [&](uint32_t x0, uint32_t y0, uint32_t x1, uint32_t y1, uint32_t off) {
      uint32_t a0, a1, a2, a3;
      XORZ(a0, x0); XORZ(a1, y0); XORZ(a2, x1); XORZ(a3, y1);
      WG_FENCE(); wgmma_n128_lo(acc, a0, a1, a2, a3, dbase + (off >> 4)); wgmma_n128_hi(acc, a0, a1, a2, a3, dbase + ((off + 2 * 8192) >> 4)); WG_COMMIT();
    };
    uint32_t ni0 = 0, ni1 = 0;
    uint32_t sidx = sidx0 + 8;
    #pragma unroll 1
    for (int f = 0; f < 12; f++) {
      const uint32_t odd = f & 1, ph = (f >> 1) & 1;
      const uint32_t db = dbase + odd * (2 * STAGE >> 4);
      const uint32_t bfull = sb + BAR_FULL + odd * 16;
      #pragma unroll
      for (int j = 0; j < 4; j++) {
        Half& h = R[j];
        if ((j & 1) == 0) mbar_wait(bfull + (j >> 1) * 8, ph);
        const uint32_t off = (j >> 1) * STAGE + (j & 1) * 4096;
        {
          uint32_t a0, a1, a2, a3, b0, b1_, b2_, b3;
          XORZ(a0, h.x.x); XORZ(a1, h.y.x); XORZ(a2, h.x.y); XORZ(a3, h.y.y);
          XORZ(b0, h.x.z); XORZ(b1_, h.y.z); XORZ(b2_, h.x.w); XORZ(b3, h.y.w);
          WG_FENCE();
          wgmma_n128_lo(acc, a0, a1, a2, a3, db + (off >> 4));
          wgmma_n128_hi(acc, a0, a1, a2, a3, db + ((off + 2 * 8192) >> 4));
          wgmma_n128_lo(acc, b0, b1_, b2_, b3, db + ((off + 2048) >> 4));
          wgmma_n128_hi(acc, b0, b1_, b2_, b3, db + ((off + 2048 + 2 * 8192) >> 4));
          WG_COMMIT();
        }
        refill(h, j);
        if (j == 2) {
          ni0 = lds32(sidx); ni1 = lds32(sidx + 8 * kF * 4);
          if (f < 10) sidx += 4;
        }
        if (j == 3) setptr(ni0, ni1);
        WG_WAIT(1);
        if (j == 0) { if (w == 0 && f > 0) { if (elect_one()) mbar_arrive(sb + BAR_EMPTY + (odd ^ 1) * 16 + 8); } }
        if (j == 2) { if (w == 0) { if (elect_one()) { mbar_arrive(sb + BAR_EMPTY + odd * 16); if (f == 11) mbar_arrive(sb + BAR_FREE2); if (f == PNGO && c == 0) mbar_arrive(sb + BAR_GO); } } }
      }
    }
    WG_WAIT(0);
    if (w == 0) { if (elect_one()) mbar_arrive(sb + BAR_FREE3); }
    {
    const uint32_t tid2 = rd_tid();
    const int t = tid2 - 128, lane = t & 31, g = lane >> 2, q = lane & 3;
    if (t == 0) STAMP(4);
    mbar_wait(sb + BAR_FULL + 0, 0);
    mbar_wait(sb + BAR_FULL + 8, 0);
    uint32_t fr[8][4];
    #pragma unroll
    for (int hh = 0; hh < 4; hh++) {
      Half& h = R[hh];
      XORZ(fr[2 * hh][0], h.x.x); XORZ(fr[2 * hh][1], h.y.x); XORZ(fr[2 * hh][2], h.x.y); XORZ(fr[2 * hh][3], h.y.y);
      XORZ(fr[2 * hh + 1][0], h.x.z); XORZ(fr[2 * hh + 1][1], h.y.z); XORZ(fr[2 * hh + 1][2], h.x.w); XORZ(fr[2 * hh + 1][3], h.y.w);
    }
    WG_FENCE();
    #pragma unroll
    for (int v = 0; v < 8; v++)
      wgmma_n128_lo(acc, fr[v][0], fr[v][1], fr[v][2], fr[v][3], dbase + (((v >> 2) * STAGE + ((v >> 1) & 1) * 4096 + (v & 1) * 2048) >> 4));
    WG_COMMIT();
    asm volatile("barrier.cluster.wait.aligned;" ::: "memory");
    uint32_t rdst, rbar;
    asm("mapa.shared::cluster.u32 %0, %1, %2;" : "=r"(rdst) : "r"(sb + OFF_RECV + t * 16), "r"(kh ^ 1));
    asm("mapa.shared::cluster.u32 %0, %1, %2;" : "=r"(rbar) : "r"(sb + BAR_RECV + (c * 4 + w) * 8), "r"(kh ^ 1));
    {
      #pragma unroll
      for (int v = 0; v < 8; v++)
        wgmma_n128_hi(acc, fr[v][0], fr[v][1], fr[v][2], fr[v][3], dbase + ((((v >> 2) * STAGE + ((v >> 1) & 1) * 4096 + (v & 1) * 2048 + 2 * 8192)) >> 4));
      WG_COMMIT();
      WG_WAIT(1);
      if (w == 0) { if (elect_one()) mbar_arrive(sb + BAR_FREES); }
      fence_acc<0, 64>(acc);
      auto ship = [&](int j) {
        asm volatile("st.async.weak.shared::cluster.mbarrier::complete_tx::bytes.v4.b32 [%0], {%1,%2,%3,%4}, [%5];"
          :: "r"(rdst + j * 4096), "r"(pack_bf16(acc[8 * j], acc[8 * j + 1])), "r"(pack_bf16(acc[8 * j + 2], acc[8 * j + 3])),
             "r"(pack_bf16(acc[8 * j + 4], acc[8 * j + 5])), "r"(pack_bf16(acc[8 * j + 6], acc[8 * j + 7])), "r"(rbar) : "memory");
      };
      ship(0); ship(1); ship(2); ship(3);
      WG_WAIT(0);
      if (w == 0) { if (elect_one()) mbar_arrive(sb + BAR_FREE01); }
      ship(4); ship(5); ship(6); ship(7);
    }
    fence_acc<64, 128>(acc);
    if (t == 0) STAMP(5);
    asm volatile("bar.sync 3, 384;" ::: "memory");
    float wt[16];
    if (NPNN > 0) {
      #pragma unroll
      for (int i = 0; i < 4; i++)
        asm volatile("ld.shared.v4.f32 {%0,%1,%2,%3}, [%4];" : "=f"(wt[4 * i]), "=f"(wt[4 * i + 1]), "=f"(wt[4 * i + 2]), "=f"(wt[4 * i + 3]) : "r"(sb + OFF_WTS + (((w & 1) * 4 + i) * 32 + lane) * 16));
    }
    mbar_wait(sb + BAR_RECV + (c * 4 + w) * 8, 0);
    if (t == 0) STAMP(6);
    float s0a = 0.f, s0b = 0.f, s1a = 0.f, s1b = 0.f;
    #pragma unroll
    for (int j = 0; j < 8; j++) {
      uint32_t rv[4];
      asm volatile("ld.shared.v4.u32 {%0,%1,%2,%3}, [%4];" : "=r"(rv[0]), "=r"(rv[1]), "=r"(rv[2]), "=r"(rv[3]) : "r"(sb + OFF_RECV + j * 4096 + t * 16));
      #pragma unroll
      for (int m = 0; m < 2; m++) {
        float wa, wb;
        asm volatile("ld.shared.v2.f32 {%0,%1}, [%2];" : "=f"(wa), "=f"(wb) : "r"(sb + OFF_W2 + ((2 * j + m) * 8 + q * 2) * 4));
        #pragma unroll
        for (int e = 0; e < 4; e++) {
          const int a = 64 + 8 * j + 4 * m + e;
          const uint32_t pk = rv[2 * m + (e >> 1)];
          const float x = acc[a] + ((e & 1) ? bf_hi(pk) : bf_lo(pk));
          const float u = x * fmaf(x * x, 0.0356774081363001f, 0.7978845608028654f);
          float th; asm("tanh.approx.f32 %0, %1;" : "=f"(th) : "f"(u));
          const float gl = fmaf(x, th, x);
          if (e == 0) s0a = fmaf(gl, wa, s0a); else if (e == 1) s0b = fmaf(gl, wb, s0b); else if (e == 2) s1a = fmaf(gl, wa, s1a); else s1b = fmaf(gl, wb, s1b);
        }
      }
    }
    float s0 = s0a + s0b, s1 = s1a + s1b;
    s0 += __shfl_xor_sync(0xffffffffu, s0, 1); s1 += __shfl_xor_sync(0xffffffffu, s1, 1);
    s0 += __shfl_xor_sync(0xffffffffu, s0, 2); s1 += __shfl_xor_sync(0xffffffffu, s1, 2);
    if (t == 0) STAMP(7);
    const int me = nh * 2 + kh, owner = c * 2 + (w >> 1);
    const int rl = (w & 1) * 16 + g;
    if (owner == me) {
      if (q == 0) {
        asm volatile("st.shared.f32 [%0], %1;" :: "r"(sb + OFF_PART + rl * 4), "f"(s0) : "memory");
        asm volatile("st.shared.f32 [%0], %1;" :: "r"(sb + OFF_PART + (rl + 8) * 4), "f"(s1) : "memory");
      }
      asm volatile("bar.arrive 2, 96;" ::: "memory");
    } else if (q == 0) {
      unsigned long long* sl = g_slots + ((mt * 4 + owner) * 4 + me) * 32 + rl;
      asm volatile("st.relaxed.gpu.global.b64 [%0], %1;" :: "l"(sl), "l"((1ull << 32) | __float_as_uint(s0)) : "memory");
      asm volatile("st.relaxed.gpu.global.b64 [%0], %1;" :: "l"(sl + 8), "l"((1ull << 32) | __float_as_uint(s1)) : "memory");
    }
    if (NPNN > 0) {
      if (NREUSE) pnn_triple2(sb, wt, w, lane, NSTAT + 2 + c); else pnn_triple(sb, wt, w, lane, NSTAT + c);
    }
    }
  } else if (warp >= 12) {
    asm volatile("bar.sync 0, 512;" ::: "memory");
    asm volatile("barrier.cluster.arrive.relaxed.aligned;" ::: "memory");
    asm volatile("setmaxnreg.dec.sync.aligned.u32 56;");
    const int lane = tid & 31;
    if (warp == 12) {
    auto load_stage = [&](int k) {
      const int s = k & 3;
      if (elect_one()) {
        mbar_expect_tx(sb + BAR_FULL + s * 8, STAGE);
        #pragma unroll
        for (int ww = 0; ww < 4; ww++)
          tma_w1(sb + s * STAGE + ww * 8192, &tmW, sb + BAR_FULL + s * 8, nh * 256 + ((ww ^ (kh ? 0 : 2)) << 6), f0 * 4 + k * 2);
      }
    };
#define W1STAG 1
    #pragma unroll
    for (int k = EARLYW1; k < NST; k++) {
      if (W1STAG > 0 && k >= W1STAG) mbar_wait(sb + BAR_FULL + (k - W1STAG) * 8, 0);
      load_stage(k);
    }
    auto prefetch_field = [&](int nf) {
      #pragma unroll
      for (int u = 0; u < 4; u++) {
        const uint32_t id = lds32(sb + OFF_IDX + ((nh * 64 + u * 16 + (lane >> 1)) * kF + f0 + nf) * 4);
        asm volatile("prefetch.global.L2 [%0];" :: "l"(table + (size_t)(id * 2u + (lane & 1)) * 128u));
      }
    };
    if (PFD > 0) { mbar_wait(sb + BAR_IDX, 0); if (PF0) prefetch_field(1); }
    int pfn = 2;
    #pragma unroll 1
    for (int k = NST; k < 26; k++) {
      mbar_wait(sb + BAR_EMPTY + (k & 3) * 8, ((k >> 2) - 1) & 1);
      load_stage(k);
      if (PFD > 0) {
        const int step = k - NST, want = min(12, min(2 + step, (step >> 1) + PFD));
        while (pfn <= want) prefetch_field(pfn++);
      }
    }
      {
        const int me = nh * 2 + kh;
        float v = __bfloat162float(b2[0]);
        if (NHELP > 0 && lane >= OWN && NPNN > 0) {
          unsigned long long* hp = g_pnn + mt * 128 + me * 32 + lane;
          unsigned long long u; int it = 0;
          do { asm volatile("ld.relaxed.gpu.global.b64 %0, [%1];" : "=l"(u) : "l"(hp) : "memory"); if (++it > 4000000) __trap(); } while ((u >> 32) == 0);
          v += __uint_as_float((uint32_t)u);
          asm volatile("st.relaxed.gpu.global.b64 [%0], %1;" :: "l"(hp), "l"(0ull) : "memory");
        }
        __syncwarp();
        asm volatile("bar.sync 2, 96;" ::: "memory");
        { float pv; asm volatile("ld.shared.f32 %0, [%1];" : "=f"(pv) : "r"(sb + OFF_PART + lane * 4)); v += pv; }
        unsigned long long* sl = g_slots + ((mt * 4 + me) * 4) * 32 + lane;
        #pragma unroll
        for (int src = 0; src < 4; src++) {
          if (src == me) continue;
          unsigned long long u; int it = 0;
          do { asm volatile("ld.relaxed.gpu.global.b64 %0, [%1];" : "=l"(u) : "l"(sl + src * 32) : "memory"); if (++it > 4000000) __trap(); } while ((u >> 32) == 0);
          v += __uint_as_float((uint32_t)u);
          asm volatile("st.relaxed.gpu.global.b64 [%0], %1;" :: "l"(sl + src * 32), "l"(0ull) : "memory");
        }
        __syncwarp();
        if (NPNN > 0) {
          mbar_wait(sb + BAR_PALL, 0);
          if (lane < OWN) { float pa, pb; asm volatile("ld.shared.v2.f32 {%0, %1}, [%2];" : "=f"(pa), "=f"(pb) : "r"(sb + OFF_PART + 128 + lane * 8)); v += pa + pb; }
        }
        out[mt * 128 + me * 32 + lane] = __float2bfloat16(v);
        if (lane == 0) { STAMP(9); GSTAMP(10); }
      }
    } else if (NPNN > 0) {
      mbar_wait(sb + BAR_IDX, 0);
      #pragma unroll 1
      for (int i = warp - 13; i < NPAIR - 4; i += 3) pnn_stage(sb, table, (nh * 2 + kh) * 32, lane, i < NSTAT + 4 ? i : i + 4);
      asm volatile("cp.async.wait_all;" ::: "memory");
    }
    asm volatile("barrier.cluster.wait.aligned;" ::: "memory");
  } else {
    const int w = warp, lane = tid & 31, g = lane >> 2, q = lane & 3;
    asm volatile("bar.sync 0, 512;" ::: "memory");
    asm volatile("barrier.cluster.arrive.relaxed.aligned;" ::: "memory");
    asm volatile("setmaxnreg.dec.sync.aligned.u32 72;");
    asm volatile("st.shared.f32 [%0], %1;" :: "r"(sb + OFF_W2 + tid * 4), "f"(0.5f * __bfloat162float(w2[nh * 256 + kh * 128 + tid])) : "memory");
    float wt[16];
    pnn_load_weights(wt, w_p, w, lane);
    #pragma unroll
    for (int i = 0; i < 4; i++)
      if (w < 2) asm volatile("st.shared.v4.f32 [%0], {%1,%2,%3,%4};" :: "r"(sb + OFF_WTS + ((w * 4 + i) * 32 + lane) * 16), "f"(wt[4 * i]), "f"(wt[4 * i + 1]), "f"(wt[4 * i + 2]), "f"(wt[4 * i + 3]) : "memory");
    asm volatile("bar.arrive 3, 384;" ::: "memory");
    for (int i = tid; i < 2 * 2 * 6 * 8; i += 128) {
      const int cc = i & 7, r6 = (i >> 3) % 6, uh = i / 48;
      asm volatile("st.shared.v4.u32 [%0], {%1,%1,%1,%1};" :: "r"(sb + OFF_STAT + (uh & 1) * 8192 + ((uh >> 1) * 32 + kF + r6) * 128 + cc * 16), "r"(0u) : "memory");
    }
    asm volatile("bar.sync 1, 128;" ::: "memory");
    if (NPNN > 0) {
      #pragma unroll 1
      for (int p = 0; p < NSTAT - 1; p++) pnn_pair(sb, wt, w, lane, p);
      if (NREUSE) { pnn_pair(sb, wt, w, lane, NSTAT); pnn_pair(sb, wt, w, lane, NSTAT + 1); }
      pnn_stage(sb, table, (nh * 2 + kh) * 32, lane, NSTAT + 4 + w);
      if (PNLATE) mbar_wait(sb + BAR_FREE01, 0);
      if (NREUSE) { pnn_pair(sb, wt, w, lane, NSTAT - 1); pnn_pair(sb, wt, w, lane, NSTAT + 8); pnn_pair(sb, wt, w, lane, NSTAT + 9); }
      else {
        #pragma unroll 1
        for (int p = NSTAT - 1; p < NPAIR; p += 3) pnn_pair(sb, wt, w, lane, p);
      }
      asm volatile("cp.async.wait_all;" ::: "memory");
    }
    if (tid == 0) STAMP(8);
    asm volatile("barrier.cluster.wait.aligned;" ::: "memory");
  }
}

#define W1PROMO CU_TENSOR_MAP_L2_PROMOTION_L2_128B
typedef CUresult (*EncodeFn)(CUtensorMap*, CUtensorMapDataType, cuuint32_t, void*, const cuuint64_t*, const cuuint64_t*, const cuuint32_t*,
                             const cuuint32_t*, CUtensorMapInterleave, CUtensorMapSwizzle, CUtensorMapL2promotion, CUtensorMapFloatOOBfill);
}

extern "C" void kernel_launch(void* const* d_in, const int* in_sizes, int n_in, void* d_out, int out_size) {
  (void)in_sizes; (void)n_in; (void)out_size;
  static EncodeFn enc = nullptr;
  if (!enc) {
    void* fn = nullptr; cudaDriverEntryPointQueryResult qr;
    cudaGetDriverEntryPoint("cuTensorMapEncodeTiled", &fn, cudaEnableDefault, &qr);
    enc = (EncodeFn)fn;
    cudaFuncSetAttribute(pnn_mlp_kernel, cudaFuncAttributeMaxDynamicSharedMemorySize, SMEM_BYTES);
  }
  CUtensorMap tm;
  cuuint64_t dims[5] = {512, 2, 4, 4, 104};
  cuuint64_t strides[4] = {1024, 8 * 1024, 2 * 1024, 32 * 1024};
  cuuint32_t box[5] = {64, 2, 4, 4, 2};
  cuuint32_t es[5] = {1, 1, 1, 1, 1};
  enc(&tm, CU_TENSOR_MAP_DATA_TYPE_BFLOAT16, 5, d_in[3], dims, strides, box, es, CU_TENSOR_MAP_INTERLEAVE_NONE, CU_TENSOR_MAP_SWIZZLE_128B,
      W1PROMO, CU_TENSOR_MAP_FLOAT_OOB_FILL_NONE);
  cudaLaunchConfig_t cfg = {};
  cfg.gridDim = dim3(128 + NHELP); cfg.blockDim = dim3(512); cfg.dynamicSmemBytes = SMEM_BYTES; cfg.stream = cudaStreamPerThread;
  cudaLaunchAttribute at[1];
  at[0].id = cudaLaunchAttributeClusterDimension; at[0].val.clusterDim.x = 2; at[0].val.clusterDim.y = 1; at[0].val.clusterDim.z = 1;
  cfg.attrs = at; cfg.numAttrs = 1;
  cudaLaunchKernelEx(&cfg, pnn_mlp_kernel, tm, (const int*)d_in[0], (const char*)d_in[1], (const __nv_bfloat16*)d_in[2],
                     (const __nv_bfloat16*)d_in[4], (const __nv_bfloat16*)d_in[5], (const __nv_bfloat16*)d_in[6], (__nv_bfloat16*)d_out, (const void*)d_in[3], 0u);
}
```

```cpp
#include <cuda_runtime.h>
#include <cuda_bf16.h>
#include <cuda.h>
#include <stdint.h>

namespace {

constexpr int kF = 26;
constexpr int NST = 4;
constexpr uint32_t STAGE = 32768;
constexpr uint32_t PCELL = 16384;
constexpr uint32_t OFF_RECV = NST * STAGE;
constexpr uint32_t OFF_STAT = OFF_RECV + 32768;
constexpr uint32_t OFF_IDX  = OFF_STAT + PCELL;
constexpr uint32_t OFF_WTS  = OFF_IDX + 128 * kF * 4;
constexpr uint32_t OFF_W2   = OFF_WTS + 4096;
constexpr uint32_t OFF_PART = OFF_W2 + 512;
constexpr uint32_t OFF_BAR  = OFF_PART + 384;
constexpr uint32_t SMEM_USED = OFF_BAR + 47 * 8;
static_assert(SMEM_USED <= 199680, "keep the 196 KB carve-out (60 KB of L1)");
constexpr uint32_t SMEM_BYTES = SMEM_USED;
constexpr uint32_t BAR_FULL = OFF_BAR, BAR_EMPTY = OFF_BAR + 32, BAR_IDX = OFF_BAR + 64, BAR_RECV = OFF_BAR + 72;
constexpr uint32_t BAR_GO = OFF_BAR + 136, BAR_FREE2 = OFF_BAR + 144, BAR_FREE3 = OFF_BAR + 152, BAR_FREE01 = OFF_BAR + 160;
constexpr uint32_t BAR_PFULL = OFF_BAR + 168, BAR_PDONE = BAR_PFULL + 16 * 8, BAR_PALL = BAR_PDONE + 8 * 8, BAR_FREES = BAR_PALL + 8;
constexpr int NHELP = 4;
constexpr int OWN = 26, NPAIR = OWN / 2;
constexpr int NEXT = 32 - OWN;
constexpr int PNGO = 3;

__device__ unsigned long long g_slots[32 * 4 * 4 * 32];
__device__ unsigned long long g_pnn[4096];

__device__ __forceinline__ void wgmma_n128_lo(float (&d)[128], uint32_t a0, uint32_t a1, uint32_t a2, uint32_t a3, uint32_t dlo) {
  asm volatile("{\n.reg .b64 db;\nmov.b64 db, {%68, 0x40000040};\n"
    "wgmma.mma_async.sync.aligned.m64n128k16.f32.bf16.bf16 "
    "{%0, %1, %2, %3, %4, %5, %6, %7, %8, %9, %10, %11, %12, %13, %14, %15, %16, %17, %18, %19, %20, %21, %22, %23, %24, %25, %26, %27, %28, %29, %30, %31, %32, %33, %34, %35, %36, %37, %38, %39, %40, %41, %42, %43, %44, %45, %46, %47, %48, %49, %50, %51, %52, %53, %54, %55, %56, %57, %58, %59, %60, %61, %62, %63}, "
    "{%64, %65, %66, %67}, db, 1, 1, 1, 1;\n}\n"
    : "+f"(d[0]), "+f"(d[1]), "+f"(d[2]), "+f"(d[3]), "+f"(d[4]), "+f"(d[5]), "+f"(d[6]), "+f"(d[7]), "+f"(d[8]), "+f"(d[9]), "+f"(d[10]), "+f"(d[11]), "+f"(d[12]), "+f"(d[13]), "+f"(d[14]), "+f"(d[15]), "+f"(d[16]), "+f"(d[17]), "+f"(d[18]), "+f"(d[19]), "+f"(d[20]), "+f"(d[21]), "+f"(d[22]), "+f"(d[23]), "+f"(d[24]), "+f"(d[25]), "+f"(d[26]), "+f"(d[27]), "+f"(d[28]), "+f"(d[29]), "+f"(d[30]), "+f"(d[31]), "+f"(d[32]), "+f"(d[33]), "+f"(d[34]), "+f"(d[35]), "+f"(d[36]), "+f"(d[37]), "+f"(d[38]), "+f"(d[39]), "+f"(d[40]), "+f"(d[41]), "+f"(d[42]), "+f"(d[43]), "+f"(d[44]), "+f"(d[45]), "+f"(d[46]), "+f"(d[47]), "+f"(d[48]), "+f"(d[49]), "+f"(d[50]), "+f"(d[51]), "+f"(d[52]), "+f"(d[53]), "+f"(d[54]), "+f"(d[55]), "+f"(d[56]), "+f"(d[57]), "+f"(d[58]), "+f"(d[59]), "+f"(d[60]), "+f"(d[61]), "+f"(d[62]), "+f"(d[63])
    : "r"(a0), "r"(a1), "r"(a2), "r"(a3), "r"(dlo));
}
__device__ __forceinline__ void wgmma_n128_hi(float (&d)[128], uint32_t a0, uint32_t a1, uint32_t a2, uint32_t a3, uint32_t dlo) {
  asm volatile("{\n.reg .b64 db;\nmov.b64 db, {%68, 0x40000040};\n"
    "wgmma.mma_async.sync.aligned.m64n128k16.f32.bf16.bf16 "
    "{%0, %1, %2, %3, %4, %5, %6, %7, %8, %9, %10, %11, %12, %13, %14, %15, %16, %17, %18, %19, %20, %21, %22, %23, %24, %25, %26, %27, %28, %29, %30, %31, %32, %33, %34, %35, %36, %37, %38, %39, %40, %41, %42, %43, %44, %45, %46, %47, %48, %49, %50, %51, %52, %53, %54, %55, %56, %57, %58, %59, %60, %61, %62, %63}, "
    "{%64, %65, %66, %67}, db, 1, 1, 1, 1;\n}\n"
    : "+f"(d[64]), "+f"(d[65]), "+f"(d[66]), "+f"(d[67]), "+f"(d[68]), "+f"(d[69]), "+f"(d[70]), "+f"(d[71]), "+f"(d[72]), "+f"(d[73]), "+f"(d[74]), "+f"(d[75]), "+f"(d[76]), "+f"(d[77]), "+f"(d[78]), "+f"(d[79]), "+f"(d[80]), "+f"(d[81]), "+f"(d[82]), "+f"(d[83]), "+f"(d[84]), "+f"(d[85]), "+f"(d[86]), "+f"(d[87]), "+f"(d[88]), "+f"(d[89]), "+f"(d[90]), "+f"(d[91]), "+f"(d[92]), "+f"(d[93]), "+f"(d[94]), "+f"(d[95]), "+f"(d[96]), "+f"(d[97]), "+f"(d[98]), "+f"(d[99]), "+f"(d[100]), "+f"(d[101]), "+f"(d[102]), "+f"(d[103]), "+f"(d[104]), "+f"(d[105]), "+f"(d[106]), "+f"(d[107]), "+f"(d[108]), "+f"(d[109]), "+f"(d[110]), "+f"(d[111]), "+f"(d[112]), "+f"(d[113]), "+f"(d[114]), "+f"(d[115]), "+f"(d[116]), "+f"(d[117]), "+f"(d[118]), "+f"(d[119]), "+f"(d[120]), "+f"(d[121]), "+f"(d[122]), "+f"(d[123]), "+f"(d[124]), "+f"(d[125]), "+f"(d[126]), "+f"(d[127])
    : "r"(a0), "r"(a1), "r"(a2), "r"(a3), "r"(dlo));
}


__device__ __forceinline__ uint32_t smem_u32(const void* p) { return (uint32_t)__cvta_generic_to_shared(p); }
__device__ __forceinline__ void mbar_init(uint32_t bar, uint32_t cnt) { asm volatile("mbarrier.init.shared::cta.b64 [%0], %1;" :: "r"(bar), "r"(cnt)); }
__device__ __forceinline__ void mbar_expect_tx(uint32_t bar, uint32_t bytes) { asm volatile("mbarrier.arrive.expect_tx.shared::cta.b64 _, [%0], %1;" :: "r"(bar), "r"(bytes) : "memory"); }
__device__ __forceinline__ void mbar_arrive(uint32_t bar) { asm volatile("mbarrier.arrive.shared::cta.b64 _, [%0];" :: "r"(bar) : "memory"); }
__device__ __forceinline__ void mbar_wait(uint32_t bar, uint32_t parity) {
  asm volatile("{\n.reg .pred p;\n.reg .u32 c;\nmov.u32 c, 0;\n"
    "LAB_WAIT:\nmbarrier.try_wait.parity.shared::cta.b64 p, [%0], %1;\n@p bra.uni LAB_DONE;\n"
    "add.u32 c, c, 1;\nsetp.lt.u32 p, c, 4000000;\n@p bra.uni LAB_WAIT;\ntrap;\nLAB_DONE:\n}" :: "r"(bar), "r"(parity) : "memory");
}
__device__ __forceinline__ uint32_t desc_lo(uint32_t addr) { return ((addr & 0x3FFFF) >> 4) | ((8192u >> 4) << 16); }
__device__ __forceinline__ uint4 ldg128_line(const void* p) {
  uint4 v;
  asm volatile("ld.global.nc.L1::no_allocate.L2::128B.v4.u32 {%0,%1,%2,%3}, [%4];" : "=r"(v.x), "=r"(v.y), "=r"(v.z), "=r"(v.w) : "l"(p));
  return v;
}
__device__ __forceinline__ uint4 ldg128_row(const void* p) {
  uint4 v;
  asm volatile("ld.global.nc.L1::no_allocate.L2::256B.v4.u32 {%0,%1,%2,%3}, [%4];" : "=r"(v.x), "=r"(v.y), "=r"(v.z), "=r"(v.w) : "l"(p));
  return v;
}
__device__ __forceinline__ uint32_t lds32(uint32_t a) { uint32_t v; asm volatile("ld.shared.u32 %0, [%1];" : "=r"(v) : "r"(a)); return v; }
__device__ __forceinline__ void tma_w1(uint32_t dst, const CUtensorMap* tm, uint32_t bar, int x, int kb) {
  asm volatile("cp.async.bulk.tensor.5d.shared::cluster.global.mbarrier::complete_tx::bytes [%0], [%1, {%3, %4, %4, %4, %5}], [%2];"
    :: "r"(dst), "l"(tm), "r"(bar), "r"(x), "r"(0), "r"(kb) : "memory");
}
__device__ __forceinline__ float bf_lo(uint32_t v) { return __uint_as_float(v << 16); }
__device__ __forceinline__ float bf_hi(uint32_t v) { return __uint_as_float(v & 0xffff0000u); }
__device__ __forceinline__ uint32_t pack_bf16(float lo, float hi) { uint32_t r; asm("cvt.rn.bf16x2.f32 %0, %1, %2;" : "=r"(r) : "f"(hi), "f"(lo)); return r; }
__device__ __forceinline__ void mma16816(float (&d)[4], uint32_t a0, uint32_t a1, uint32_t a2, uint32_t a3, uint32_t b0, uint32_t b1) {
  asm volatile("mma.sync.aligned.m16n8k16.row.col.f32.bf16.bf16.f32 {%0,%1,%2,%3}, {%4,%5,%6,%7}, {%8,%9}, {%0,%1,%2,%3};"
    : "+f"(d[0]), "+f"(d[1]), "+f"(d[2]), "+f"(d[3]) : "r"(a0), "r"(a1), "r"(a2), "r"(a3), "r"(b0), "r"(b1));
}

__device__ __forceinline__ uint32_t rd_tid() { uint32_t v; asm volatile("mov.u32 %0, %tid.x;" : "=r"(v)); return v; }
template <int LO, int HI> __device__ __forceinline__ void fence_acc(float (&d)[128]) {
  #pragma unroll
  for (int i = LO; i < HI; i++) asm volatile("" : "+f"(d[i]) :: "memory");
}
__device__ __forceinline__ bool elect_one() {
  uint32_t p; asm volatile("{\n.reg .pred P;\nelect.sync _|P, 0xffffffff;\nselp.u32 %0, 1, 0, P;\n}" : "=r"(p)); return p != 0;
}
constexpr int NSTAT = NPAIR - 8;
__device__ __forceinline__ void cp16(uint32_t dst, const void* src) { asm volatile("cp.async.cg.shared.global [%0], [%1], 16;" :: "r"(dst), "l"(src) : "memory"); }
__device__ __forceinline__ uint32_t pnn_cell(uint32_t sb, int p) {
  if (p < NSTAT) return sb + OFF_STAT;
  p -= NSTAT;
  return p < 4 ? sb + (p + 4) * PCELL : sb + (p & 1) * 2 * PCELL + (p >= 6 ? PCELL : 0);
}
__device__ __forceinline__ uint32_t pnn_gate(int p) {
  if (p == 0) return BAR_GO;
  if (p < NSTAT) return BAR_PDONE + (p - 1) * 8;
  const int j = p - NSTAT;
  return j < 2 ? BAR_FREE2 : (j < 4 ? BAR_FREE3 : (j < 6 ? BAR_FREES : BAR_FREE01));
}
__device__ __forceinline__ void pnn_stage(uint32_t sb, const char* __restrict__ table, int row0, int lane, int p) {
  const uint32_t half = lane >> 4, ch = lane & 15;
  const uint32_t cell = pnn_cell(sb, p) + (ch >> 3) * 8192 + half * 128, x0 = (ch & 7) ^ half;
  const uint32_t srw = sb + OFF_IDX + ((row0 + 2 * p) * kF + half) * 4;
  mbar_wait(sb + pnn_gate(p), 0);
  uint32_t ids[26];
  #pragma unroll
  for (int i = 0; i < 26; i++) ids[i] = lds32(srw + (i / 13) * kF * 4 + (i % 13) * 8);
  #pragma unroll
  for (int i = 0; i < 26; i++)
    cp16(cell + (i / 13) * 4096 + (i % 13) * 256 + ((x0 ^ (((i % 13) & 3) * 2)) << 4), table + (size_t)(ids[i] * 16u + ch) * 16u);
  asm volatile("cp.async.mbarrier.arrive.noinc.shared::cta.b64 [%0];" :: "r"(sb + BAR_PFULL + p * 8) : "memory");
}
__device__ __forceinline__ void wgmma_gram(float (&d)[32], uint32_t dlo, int acc) {
  asm volatile("{\n.reg .pred p;\n.reg .b64 db;\nsetp.ne.b32 p, %33, 0;\nmov.b64 db, {%32, 0x40000040};\n"
    "wgmma.mma_async.sync.aligned.m64n64k16.f32.bf16.bf16 "
    "{%0,%1,%2,%3,%4,%5,%6,%7,%8,%9,%10,%11,%12,%13,%14,%15,%16,%17,%18,%19,%20,%21,%22,%23,%24,%25,%26,%27,%28,%29,%30,%31}, db, db, p, 1, 1, 0, 0;\n}\n"
    : "+f"(d[0]), "+f"(d[1]), "+f"(d[2]), "+f"(d[3]), "+f"(d[4]), "+f"(d[5]), "+f"(d[6]), "+f"(d[7]),
      "+f"(d[8]), "+f"(d[9]), "+f"(d[10]), "+f"(d[11]), "+f"(d[12]), "+f"(d[13]), "+f"(d[14]), "+f"(d[15]),
      "+f"(d[16]), "+f"(d[17]), "+f"(d[18]), "+f"(d[19]), "+f"(d[20]), "+f"(d[21]), "+f"(d[22]), "+f"(d[23]),
      "+f"(d[24]), "+f"(d[25]), "+f"(d[26]), "+f"(d[27]), "+f"(d[28]), "+f"(d[29]), "+f"(d[30]), "+f"(d[31])
    : "r"(dlo), "r"(acc));
}

__device__ __forceinline__ void pnn_issue(float (&D)[32], uint32_t sb, int p) {
  mbar_wait(sb + BAR_PFULL + p * 8, 0);
  asm volatile("fence.proxy.async.shared::cta;" ::: "memory");
  const uint32_t dl = ((pnn_cell(sb, p) & 0x3FFFF) >> 4) | (1u << 16);
  asm volatile("wgmma.fence.sync.aligned;" ::: "memory");
  #pragma unroll
  for (int kk = 0; kk < 8; kk++) wgmma_gram(D, dl + (((kk >> 2) * 8192 + (kk & 3) * 32) >> 4), kk > 0);
  asm volatile("wgmma.commit_group.sync.aligned;" ::: "memory");
}
__device__ __forceinline__ float pnn_dot(float (&D)[32], const float (&wt)[16], int w, int lane) {
  const bool pc = (lane & 3) == 0, pr = !(w & 1) || lane < 8;
  #pragma unroll
  for (int i = 0; i < 32; i++) asm volatile("" : "+f"(D[i]) :: "memory");
  float s4[4] = {0.f, 0.f, 0.f, 0.f};
  if (w >> 1) {
    #pragma unroll
    for (int i = 0; i < 16; i++) { const bool ok = ((i >> 2) < 3 || pc) && ((i & 2) == 0 || pr); if (ok) s4[i & 3] = fmaf(D[16 + i], wt[i], s4[i & 3]); }
  } else {
    #pragma unroll
    for (int i = 0; i < 16; i++) { const bool ok = ((i >> 2) < 3 || pc) && ((i & 2) == 0 || pr); if (ok) s4[i & 3] = fmaf(D[i], wt[i], s4[i & 3]); }
  }
  return (s4[0] + s4[1]) + (s4[2] + s4[3]);
}
__device__ __forceinline__ void pnn_store(uint32_t sb, float sum, int w, int lane, int p) {
  if (lane == 0) {
    asm volatile("st.shared.f32 [%0], %1;" :: "r"(sb + OFF_PART + 128 + ((2 * p + (w >> 1)) * 2 + (w & 1)) * 4), "f"(sum) : "memory");
    mbar_arrive(sb + BAR_PALL);
  }
}
__device__ __forceinline__ void pnn_pair(uint32_t sb, const float (&wt)[16], int w, int lane, int p) {
  float D[32];
  pnn_issue(D, sb, p);
  asm volatile("wgmma.wait_group.sync.aligned 0;" ::: "memory");
  if (p < NSTAT - 1 && w == 0 && lane == 0) mbar_arrive(sb + BAR_PDONE + p * 8);
  float sum = pnn_dot(D, wt, w, lane);
  #pragma unroll
  for (int o = 16; o > 0; o >>= 1) sum += __shfl_xor_sync(0xffffffffu, sum, o);
  pnn_store(sb, sum, w, lane, p);
}
__device__ __forceinline__ void pnn_triple(uint32_t sb, const float (&wt)[16], int w, int lane, int p) {
  float D0[32], D1[32], D2[32];
  pnn_issue(D0, sb, p); pnn_issue(D1, sb, p + 3); pnn_issue(D2, sb, p + 6);
  asm volatile("wgmma.wait_group.sync.aligned 2;" ::: "memory");
  float a = pnn_dot(D0, wt, w, lane);
  asm volatile("wgmma.wait_group.sync.aligned 1;" ::: "memory");
  float b = pnn_dot(D1, wt, w, lane);
  asm volatile("wgmma.wait_group.sync.aligned 0;" ::: "memory");
  float c = pnn_dot(D2, wt, w, lane);
  #pragma unroll
  for (int o = 16; o > 0; o >>= 1) { a += __shfl_xor_sync(0xffffffffu, a, o); b += __shfl_xor_sync(0xffffffffu, b, o); c += __shfl_xor_sync(0xffffffffu, c, o); }
  pnn_store(sb, a, w, lane, p); pnn_store(sb, b, w, lane, p + 3); pnn_store(sb, c, w, lane, p + 6);
}
__device__ __forceinline__ void pnn_load_weights(float (&wt)[16], const __nv_bfloat16* __restrict__ w_p, int w, int lane) {
  #pragma unroll
  for (int i = 0; i < 16; i++) {
    const int fi = (w & 1) * 16 + (lane >> 2) + 8 * ((i >> 1) & 1), fj = 8 * (i >> 2) + 2 * (lane & 3) + (i & 1);
    wt[i] = (fi < kF && fj < kF) ? __bfloat162float(w_p[fi * kF + fj]) : 0.f;
  }
}

constexpr uint32_t HCELL = kF * 256, HOFF_WTS = 28 * HCELL, HOFF_ZERO = HOFF_WTS + 3072;
__device__ __forceinline__ float helper_gram(uint32_t sb, int lane, uint32_t cell) {
  const uint32_t lrow = (lane & 7) + ((lane >> 3) & 1) * 8, lch = lane >> 4;
  float G[6][4];
  #pragma unroll
  for (int b = 0; b < 6; b++) { G[b][0] = G[b][1] = G[b][2] = G[b][3] = 0.f; }
  #pragma unroll
  for (int s = 0; s < 8; s++) {
    const uint32_t ch = 2 * s + lch;
    const uint32_t o = lrow * 256 + (ch >> 3) * 128 + (((ch & 7) ^ (lrow & 7)) << 4);
    uint32_t p0, p1, p2, p3, c0, c1, c2, c3;
    asm volatile("ldmatrix.sync.aligned.m8n8.x4.shared.b16 {%0,%1,%2,%3}, [%4];" : "=r"(p0), "=r"(p1), "=r"(p2), "=r"(p3) : "r"(cell + o));
    asm volatile("ldmatrix.sync.aligned.m8n8.x4.shared.b16 {%0,%1,%2,%3}, [%4];" : "=r"(c0), "=r"(c1), "=r"(c2), "=r"(c3)
                 : "r"(lrow < 10 ? cell + 4096 + o : sb + HOFF_ZERO));
    mma16816(G[0], p0, p1, p2, p3, p0, p2);
    mma16816(G[4], c0, c1, c2, c3, c0, c2);
    mma16816(G[1], p0, p1, p2, p3, p1, p3);
    mma16816(G[5], c0, c1, c2, c3, c1, c3);
    mma16816(G[2], p0, p1, p2, p3, c0, c2);
    mma16816(G[3], p0, p1, p2, p3, c1, c3);
  }
  float s0 = 0.f, s1 = 0.f;
  #pragma unroll
  for (int b = 0; b < 6; b++) {
    float4 wv;
    asm volatile("ld.shared.v4.f32 {%0,%1,%2,%3}, [%4];" : "=f"(wv.x), "=f"(wv.y), "=f"(wv.z), "=f"(wv.w) : "r"(sb + HOFF_WTS + (b * 32 + lane) * 16));
    s0 = fmaf(G[b][0], wv.x, s0); s1 = fmaf(G[b][1], wv.y, s1); s0 = fmaf(G[b][2], wv.z, s0); s1 = fmaf(G[b][3], wv.w, s1);
  }
  float sum = s0 + s1;
  #pragma unroll
  for (int o = 16; o > 0; o >>= 1) sum += __shfl_xor_sync(0xffffffffu, sum, o);
  return sum;
}

struct Half { uint4 x, y; };

__global__ void __cluster_dims__(2, 1, 1) __launch_bounds__(512, 1)
pnn_mlp_kernel(const __grid_constant__ CUtensorMap tmW, const int* __restrict__ idx, const char* __restrict__ table,
               const __nv_bfloat16* __restrict__ w_p, const __nv_bfloat16* __restrict__ b1, const __nv_bfloat16* __restrict__ w2,
               const __nv_bfloat16* __restrict__ b2, __nv_bfloat16* __restrict__ out, const void* __restrict__ w1g, uint32_t zero) {
  extern __shared__ __align__(1024) uint8_t smem_raw[];
  const uint32_t sb = smem_u32(smem_raw);
  if (sb & 1023u) __trap();
  const int tid = threadIdx.x;
  const int warp = __shfl_sync(0xffffffffu, tid >> 5, 0);
  if (blockIdx.x < NHELP) {
    constexpr int HW = 14, NS = 32 * NEXT;
    static_assert(HOFF_ZERO + 16 <= SMEM_BYTES, "helper smem layout");
    const int lane = tid & 31;
    auto sample_of = [&](int j) { return (blockIdx.x * 32 + j / NEXT) * 32 + OWN + j % NEXT; };
    auto ld_ids = [&](int j) { return (lane < kF && j < NS) ? __ldg(idx + (size_t)sample_of(j) * kF + lane) : 0; };
    int id0 = ld_ids(warp), id1 = ld_ids(warp + HW), id2 = ld_ids(warp + 2 * HW);
    for (int e = tid; e < 6 * 128; e += 512) {
      const int b = e >> 7, e2 = e & 3, ln = (e >> 2) & 31;
      const int fi = (b < 4 ? 0 : 16) + (e2 >> 1) * 8 + (ln >> 2), fj = (b < 4 ? b : b - 2) * 8 + (ln & 3) * 2 + (e2 & 1);
      float v = 0.f;
      if (fi < kF && fj < kF) {
        v = __bfloat162float(w_p[fi * kF + fj]);
        if (b == 2 || b == 3) v += __bfloat162float(w_p[fj * kF + fi]);
      }
      asm volatile("st.shared.f32 [%0], %1;" :: "r"(sb + HOFF_WTS + e * 4), "f"(v) : "memory");
    }
    if (tid < 4) asm volatile("st.shared.u32 [%0], %1;" :: "r"(sb + HOFF_ZERO + tid * 4), "r"(0u) : "memory");
    __syncthreads();
    if (warp < HW) {
      const uint32_t cbase = sb + warp * 2 * HCELL;
      const uint32_t half = lane >> 4, ch = lane & 15;
      const uint32_t o0 = half * 256 + (ch >> 3) * 128, x0 = (ch & 7) ^ half;
      auto stage = [&](int myid, uint32_t cell) {
        #pragma unroll
        for (int i = 0; i < 13; i++) {
          const uint32_t id = __shfl_sync(0xffffffffu, myid, 2 * i + half);
          cp16(cell + o0 + i * 512 + ((x0 ^ ((i & 3) * 2)) << 4), table + (size_t)(id * 16u + ch) * 16u);
        }
        asm volatile("cp.async.commit_group;" ::: "memory");
      };
      stage(id0, cbase);
      int buf = 0;
      #pragma unroll 1
      for (int j = warp; j < NS; j += HW) {
        if (j + HW < NS) stage(id1, cbase + (buf ^ 1) * HCELL); else asm volatile("cp.async.commit_group;" ::: "memory");
        id1 = id2; id2 = ld_ids(j + 3 * HW);
        asm volatile("cp.async.wait_group 1;" ::: "memory");
        __syncwarp();
        const float sum = helper_gram(sb, lane, cbase + buf * HCELL);
        if (lane == 0) asm volatile("st.relaxed.gpu.global.b64 [%0], %1;" :: "l"(g_pnn + sample_of(j)), "l"((1ull << 32) | __float_as_uint(sum)) : "memory");
        __syncwarp();
        buf ^= 1;
      }
    }
    return;
  }
  const int bid = blockIdx.x - NHELP;
  const int kh = bid & 1, pair = bid >> 1, nh = (pair >> 3) & 1, mt = (pair & 7) | ((pair >> 4) << 3);
  const int f0 = kh * 13;

  if (warp == 13) {
    const int l = tid & 31;
    const char* pg = l < 13 ? table + (size_t)l * (2u << 20) : (const char*)w1g + (size_t)((l - 13) & 1) * (2u << 20);
    if (l < 15) asm volatile("prefetch.global.L2 [%0];" :: "l"(pg));
  }
  if (tid == 32) asm volatile("prefetch.tensormap [%0];" :: "l"(&tmW) : "memory");
  if (tid == 0) {
    mbar_init(sb + BAR_IDX, 1);
    #pragma unroll
    for (int s = 0; s < NST; s++) { mbar_init(sb + BAR_FULL + s * 8, 1); mbar_init(sb + BAR_EMPTY + s * 8, 2); }
    #pragma unroll
    for (int w = 0; w < 8; w++) mbar_init(sb + BAR_RECV + w * 8, 1);
    #pragma unroll
    for (int p = 0; p < NPAIR; p++) mbar_init(sb + BAR_PFULL + p * 8, 32);
    #pragma unroll
    for (int p = 0; p < NSTAT; p++) mbar_init(sb + BAR_PDONE + p * 8, 1);
    mbar_init(sb + BAR_PALL, 4 * NPAIR); mbar_init(sb + BAR_FREES, 2);
    mbar_init(sb + BAR_GO, 1); mbar_init(sb + BAR_FREE2, 2); mbar_init(sb + BAR_FREE3, 2); mbar_init(sb + BAR_FREE01, 2);
    asm volatile("fence.mbarrier_init.release.cluster;" ::: "memory");
    mbar_expect_tx(sb + BAR_IDX, 128 * kF * 4);
    asm volatile("cp.async.bulk.shared::cluster.global.mbarrier::complete_tx::bytes [%0], [%1], %2, [%3];"
      :: "r"(sb + OFF_IDX), "l"(idx + (size_t)mt * 128 * kF), "r"(128 * kF * 4), "r"(sb + BAR_IDX) : "memory");
    mbar_expect_tx(sb + BAR_FULL, STAGE);
    #pragma unroll
    for (int ww = 0; ww < 4; ww++) tma_w1(sb + ww * 8192, &tmW, sb + BAR_FULL, nh * 256 + ((ww ^ (kh ? 0 : 2)) << 6), f0 * 4);
  }

  if (warp >= 4 && warp < 12) {
    const int c = (warp - 4) >> 2, w = warp & 3, lane = tid & 31, g = lane >> 2, q = lane & 3;
    const int r0 = c * 64 + w * 16 + g;
    const int* ip = idx + (size_t)(mt * 128 + r0) * kF + f0;
    const uint32_t i00 = __ldg(ip), i10 = __ldg(ip + 8 * kF), i01 = __ldg(ip + 1), i11 = __ldg(ip + 8 * kF + 1);
    uint32_t braw[16];
    {
      const uint32_t* bp = reinterpret_cast<const uint32_t*>(b1 + nh * 256 + kh * 128) + q;
      #pragma unroll
      for (int i = 0; i < 16; i++) braw[i] = __ldg(bp + i * 4);
    }
    asm volatile("bar.sync 0, 512;" ::: "memory");
    asm volatile("barrier.cluster.arrive.relaxed.aligned;" ::: "memory");
    asm volatile("setmaxnreg.inc.sync.aligned.u32 192;");
    if (elect_one()) mbar_expect_tx(sb + BAR_RECV + (c * 4 + w) * 8, 4096);

    Half R[4];
    const char *p0, *p1;
    auto setptr = [&](uint32_t i0, uint32_t i1) {
      const uint32_t qq = rd_tid() & 3;
      p0 = table + (size_t)(i0 * 16u + qq) * 16u; p1 = table + (size_t)(i1 * 16u + qq) * 16u;
    };
    auto refill = [&](Half& h, int quarter) { h.x = ldg128_row(p0 + quarter * 64); h.y = ldg128_row(p1 + quarter * 64); };
    setptr(i00, i10);
    #pragma unroll
    for (int j = 0; j < 4; j++) { R[j].x = ldg128_line(p0 + j * 64); R[j].y = ldg128_line(p1 + j * 64); }
    setptr(i01, i11);

    float acc[128];
    #pragma unroll
    for (int i = 0; i < 64; i++) acc[i] = 0.f;
    #pragma unroll
    for (int i = 0; i < 16; i++) {
      acc[64 + 4 * i + 0] = bf_lo(braw[i]); acc[64 + 4 * i + 1] = bf_hi(braw[i]);
      acc[64 + 4 * i + 2] = bf_lo(braw[i]); acc[64 + 4 * i + 3] = bf_hi(braw[i]);
    }
    fence_acc<0, 128>(acc);
    const uint32_t sidx0 = sb + OFF_IDX + (r0 * kF + f0) * 4;
    mbar_wait(sb + BAR_IDX, 0);

#define WG_FENCE()  asm volatile("wgmma.fence.sync.aligned;" ::: "memory")
#define WG_COMMIT() asm volatile("wgmma.commit_group.sync.aligned;" ::: "memory")
#define WG_WAIT(n)  asm volatile("wgmma.wait_group.sync.aligned " #n ";" ::: "memory")
#define XORZ(d, s)  asm volatile("xor.b32 %0, %1, %2;" : "=r"(d) : "r"(s), "r"(zero))
    const uint32_t dbase = desc_lo(sb);
    uint32_t ni0 = 0, ni1 = 0;
    #pragma unroll 1
    for (int f = 0; f < 12; f++) {
      const uint32_t odd = f & 1, ph = (f >> 1) & 1;
      const uint32_t db = dbase + odd * (2 * STAGE >> 4);
      const uint32_t bfull = sb + BAR_FULL + odd * 16;
      #pragma unroll
      for (int j = 0; j < 4; j++) {
        Half& h = R[j];
        if ((j & 1) == 0) mbar_wait(bfull + (j >> 1) * 8, ph);
        const uint32_t off = (j >> 1) * STAGE + (j & 1) * 4096;
        {
          uint32_t a0, a1, a2, a3, b0, b1_, b2_, b3;
          XORZ(a0, h.x.x); XORZ(a1, h.y.x); XORZ(a2, h.x.y); XORZ(a3, h.y.y);
          XORZ(b0, h.x.z); XORZ(b1_, h.y.z); XORZ(b2_, h.x.w); XORZ(b3, h.y.w);
          WG_FENCE();
          wgmma_n128_lo(acc, a0, a1, a2, a3, db + (off >> 4));
          wgmma_n128_hi(acc, a0, a1, a2, a3, db + ((off + 2 * 8192) >> 4));
          wgmma_n128_lo(acc, b0, b1_, b2_, b3, db + ((off + 2048) >> 4));
          wgmma_n128_hi(acc, b0, b1_, b2_, b3, db + ((off + 2048 + 2 * 8192) >> 4));
          WG_COMMIT();
        }
        refill(h, j);
        if (j == 2) {
          const uint32_t sidx = sidx0 + min(f + 2, 12) * 4;
          ni0 = lds32(sidx); ni1 = lds32(sidx + 8 * kF * 4);
        }
        if (j == 3) setptr(ni0, ni1);
        WG_WAIT(1);
        if (j == 0) { if (w == 0 && f > 0) { if (elect_one()) mbar_arrive(sb + BAR_EMPTY + (odd ^ 1) * 16 + 8); } }
        if (j == 2) { if (w == 0) { if (elect_one()) { mbar_arrive(sb + BAR_EMPTY + odd * 16); if (f == 11) mbar_arrive(sb + BAR_FREE2); if (f == PNGO && c == 0) mbar_arrive(sb + BAR_GO); } } }
      }
    }
    WG_WAIT(0);
    if (w == 0) { if (elect_one()) mbar_arrive(sb + BAR_FREE3); }
    {
    const uint32_t tid2 = rd_tid();
    const int t = tid2 - 128, lane = t & 31, g = lane >> 2, q = lane & 3;
    mbar_wait(sb + BAR_FULL + 0, 0);
    mbar_wait(sb + BAR_FULL + 8, 0);
    uint32_t fr[8][4];
    #pragma unroll
    for (int hh = 0; hh < 4; hh++) {
      Half& h = R[hh];
      XORZ(fr[2 * hh][0], h.x.x); XORZ(fr[2 * hh][1], h.y.x); XORZ(fr[2 * hh][2], h.x.y); XORZ(fr[2 * hh][3], h.y.y);
      XORZ(fr[2 * hh + 1][0], h.x.z); XORZ(fr[2 * hh + 1][1], h.y.z); XORZ(fr[2 * hh + 1][2], h.x.w); XORZ(fr[2 * hh + 1][3], h.y.w);
    }
    WG_FENCE();
    #pragma unroll
    for (int v = 0; v < 8; v++)
      wgmma_n128_lo(acc, fr[v][0], fr[v][1], fr[v][2], fr[v][3], dbase + (((v >> 2) * STAGE + ((v >> 1) & 1) * 4096 + (v & 1) * 2048) >> 4));
    WG_COMMIT();
    asm volatile("barrier.cluster.wait.aligned;" ::: "memory");
    uint32_t rdst, rbar;
    asm("mapa.shared::cluster.u32 %0, %1, %2;" : "=r"(rdst) : "r"(sb + OFF_RECV + t * 16), "r"(kh ^ 1));
    asm("mapa.shared::cluster.u32 %0, %1, %2;" : "=r"(rbar) : "r"(sb + BAR_RECV + (c * 4 + w) * 8), "r"(kh ^ 1));
    {
      #pragma unroll
      for (int v = 0; v < 8; v++)
        wgmma_n128_hi(acc, fr[v][0], fr[v][1], fr[v][2], fr[v][3], dbase + ((((v >> 2) * STAGE + ((v >> 1) & 1) * 4096 + (v & 1) * 2048 + 2 * 8192)) >> 4));
      WG_COMMIT();
      WG_WAIT(1);
      if (w == 0) { if (elect_one()) mbar_arrive(sb + BAR_FREES); }
      fence_acc<0, 64>(acc);
      auto ship = [&](int j) {
        asm volatile("st.async.weak.shared::cluster.mbarrier::complete_tx::bytes.v4.b32 [%0], {%1,%2,%3,%4}, [%5];"
          :: "r"(rdst + j * 4096), "r"(pack_bf16(acc[8 * j], acc[8 * j + 1])), "r"(pack_bf16(acc[8 * j + 2], acc[8 * j + 3])),
             "r"(pack_bf16(acc[8 * j + 4], acc[8 * j + 5])), "r"(pack_bf16(acc[8 * j + 6], acc[8 * j + 7])), "r"(rbar) : "memory");
      };
      ship(0); ship(1); ship(2); ship(3);
      WG_WAIT(0);
      if (w == 0) { if (elect_one()) mbar_arrive(sb + BAR_FREE01); }
      ship(4); ship(5); ship(6); ship(7);
    }
    fence_acc<64, 128>(acc);
    asm volatile("bar.sync 3, 384;" ::: "memory");
    float wt[16];
    {
      #pragma unroll
      for (int i = 0; i < 4; i++)
        asm volatile("ld.shared.v4.f32 {%0,%1,%2,%3}, [%4];" : "=f"(wt[4 * i]), "=f"(wt[4 * i + 1]), "=f"(wt[4 * i + 2]), "=f"(wt[4 * i + 3]) : "r"(sb + OFF_WTS + (((w & 1) * 4 + i) * 32 + lane) * 16));
    }
    mbar_wait(sb + BAR_RECV + (c * 4 + w) * 8, 0);
    float s0a = 0.f, s0b = 0.f, s1a = 0.f, s1b = 0.f;
    #pragma unroll
    for (int j = 0; j < 8; j++) {
      uint32_t rv[4];
      asm volatile("ld.shared.v4.u32 {%0,%1,%2,%3}, [%4];" : "=r"(rv[0]), "=r"(rv[1]), "=r"(rv[2]), "=r"(rv[3]) : "r"(sb + OFF_RECV + j * 4096 + t * 16));
      #pragma unroll
      for (int m = 0; m < 2; m++) {
        float wa, wb;
        asm volatile("ld.shared.v2.f32 {%0,%1}, [%2];" : "=f"(wa), "=f"(wb) : "r"(sb + OFF_W2 + ((2 * j + m) * 8 + q * 2) * 4));
        #pragma unroll
        for (int e = 0; e < 4; e++) {
          const int a = 64 + 8 * j + 4 * m + e;
          const uint32_t pk = rv[2 * m + (e >> 1)];
          const float x = acc[a] + ((e & 1) ? bf_hi(pk) : bf_lo(pk));
          const float u = x * fmaf(x * x, 0.0356774081363001f, 0.7978845608028654f);
          float th; asm("tanh.approx.f32 %0, %1;" : "=f"(th) : "f"(u));
          const float gl = fmaf(x, th, x);
          if (e == 0) s0a = fmaf(gl, wa, s0a); else if (e == 1) s0b = fmaf(gl, wb, s0b); else if (e == 2) s1a = fmaf(gl, wa, s1a); else s1b = fmaf(gl, wb, s1b);
        }
      }
    }
    float s0 = s0a + s0b, s1 = s1a + s1b;
    s0 += __shfl_xor_sync(0xffffffffu, s0, 1); s1 += __shfl_xor_sync(0xffffffffu, s1, 1);
    s0 += __shfl_xor_sync(0xffffffffu, s0, 2); s1 += __shfl_xor_sync(0xffffffffu, s1, 2);
    const int me = nh * 2 + kh, owner = c * 2 + (w >> 1);
    const int rl = (w & 1) * 16 + g;
    if (owner == me) {
      if (q == 0) {
        asm volatile("st.shared.f32 [%0], %1;" :: "r"(sb + OFF_PART + rl * 4), "f"(s0) : "memory");
        asm volatile("st.shared.f32 [%0], %1;" :: "r"(sb + OFF_PART + (rl + 8) * 4), "f"(s1) : "memory");
      }
      asm volatile("bar.arrive 2, 96;" ::: "memory");
    } else if (q == 0) {
      unsigned long long* sl = g_slots + ((mt * 4 + owner) * 4 + me) * 32 + rl;
      asm volatile("st.relaxed.gpu.global.b64 [%0], %1;" :: "l"(sl), "l"((1ull << 32) | __float_as_uint(s0)) : "memory");
      asm volatile("st.relaxed.gpu.global.b64 [%0], %1;" :: "l"(sl + 8), "l"((1ull << 32) | __float_as_uint(s1)) : "memory");
    }
    pnn_triple(sb, wt, w, lane, NSTAT + c);
    }
  } else if (warp >= 12) {
    asm volatile("bar.sync 0, 512;" ::: "memory");
    asm volatile("barrier.cluster.arrive.relaxed.aligned;" ::: "memory");
    asm volatile("setmaxnreg.dec.sync.aligned.u32 56;");
    const int lane = tid & 31;
    if (warp == 12) {
    auto load_stage = [&](int k) {
      const int s = k & 3;
      if (elect_one()) {
        mbar_expect_tx(sb + BAR_FULL + s * 8, STAGE);
        #pragma unroll
        for (int ww = 0; ww < 4; ww++)
          tma_w1(sb + s * STAGE + ww * 8192, &tmW, sb + BAR_FULL + s * 8, nh * 256 + ((ww ^ (kh ? 0 : 2)) << 6), f0 * 4 + k * 2);
      }
    };
    #pragma unroll
    for (int k = 1; k < NST; k++) { mbar_wait(sb + BAR_FULL + (k - 1) * 8, 0); load_stage(k); }
    #pragma unroll 1
    for (int k = NST; k < 26; k++) {
      mbar_wait(sb + BAR_EMPTY + (k & 3) * 8, ((k >> 2) - 1) & 1);
      load_stage(k);
    }
      {
        const int me = nh * 2 + kh;
        float v = __bfloat162float(b2[0]);
        unsigned long long* sl = g_slots + ((mt * 4 + me) * 4) * 32 + lane;
        unsigned long long* src[4] = {sl + ((me + 1) & 3) * 32, sl + ((me + 2) & 3) * 32, sl + ((me + 3) & 3) * 32, g_pnn + mt * 128 + me * 32 + lane};
        uint32_t pending = lane >= OWN ? 15u : 7u;
        asm volatile("bar.sync 2, 96;" ::: "memory");
        { float pv; asm volatile("ld.shared.f32 %0, [%1];" : "=f"(pv) : "r"(sb + OFF_PART + lane * 4)); v += pv; }
        float rv[4] = {0.f, 0.f, 0.f, 0.f};
        #pragma unroll 1
        for (int it = 0; pending != 0; it++) {
          unsigned long long u[4];
          #pragma unroll
          for (int i = 0; i < 4; i++) { u[i] = 0; if ((pending >> i) & 1) asm volatile("ld.relaxed.gpu.global.b64 %0, [%1];" : "=l"(u[i]) : "l"(src[i]) : "memory"); }
          #pragma unroll
          for (int i = 0; i < 4; i++)
            if (u[i] >> 32) {
              rv[i] = __uint_as_float((uint32_t)u[i]); pending &= ~(1u << i);
              asm volatile("st.relaxed.gpu.global.b64 [%0], %1;" :: "l"(src[i]), "l"(0ull) : "memory");
            }
          if (it > 4000000) __trap();
        }
        v += (rv[0] + rv[1]) + (rv[2] + rv[3]);
        __syncwarp();
        mbar_wait(sb + BAR_PALL, 0);
        if (lane < OWN) { float pa, pb; asm volatile("ld.shared.v2.f32 {%0, %1}, [%2];" : "=f"(pa), "=f"(pb) : "r"(sb + OFF_PART + 128 + lane * 8)); v += pa + pb; }
        out[mt * 128 + me * 32 + lane] = __float2bfloat16(v);
      }
    } else {
      mbar_wait(sb + BAR_IDX, 0);
      #pragma unroll 1
      for (int p = warp - 13; p < NPAIR - 4; p += 3) pnn_stage(sb, table, (nh * 2 + kh) * 32, lane, p);
      asm volatile("cp.async.wait_all;" ::: "memory");
    }
    asm volatile("barrier.cluster.wait.aligned;" ::: "memory");
  } else {
    const int w = warp, lane = tid & 31;
    asm volatile("bar.sync 0, 512;" ::: "memory");
    asm volatile("barrier.cluster.arrive.relaxed.aligned;" ::: "memory");
    asm volatile("setmaxnreg.dec.sync.aligned.u32 72;");
    asm volatile("st.shared.f32 [%0], %1;" :: "r"(sb + OFF_W2 + tid * 4), "f"(0.5f * __bfloat162float(w2[nh * 256 + kh * 128 + tid])) : "memory");
    float wt[16];
    pnn_load_weights(wt, w_p, w, lane);
    #pragma unroll
    for (int i = 0; i < 4; i++)
      if (w < 2) asm volatile("st.shared.v4.f32 [%0], {%1,%2,%3,%4};" :: "r"(sb + OFF_WTS + ((w * 4 + i) * 32 + lane) * 16), "f"(wt[4 * i]), "f"(wt[4 * i + 1]), "f"(wt[4 * i + 2]), "f"(wt[4 * i + 3]) : "memory");
    asm volatile("bar.arrive 3, 384;" ::: "memory");
    for (int i = tid; i < 2 * 2 * 6 * 8; i += 128) {
      const int cc = i & 7, r6 = (i >> 3) % 6, uh = i / 48;
      asm volatile("st.shared.v4.u32 [%0], {%1,%1,%1,%1};" :: "r"(sb + OFF_STAT + (uh & 1) * 8192 + ((uh >> 1) * 32 + kF + r6) * 128 + cc * 16), "r"(0u) : "memory");
    }
    asm volatile("bar.sync 1, 128;" ::: "memory");
    #pragma unroll 1
    for (int p = 0; p < NSTAT - 1; p++) pnn_pair(sb, wt, w, lane, p);
    pnn_stage(sb, table, (nh * 2 + kh) * 32, lane, NSTAT + 4 + w);
    mbar_wait(sb + BAR_FREE01, 0);
    #pragma unroll 1
    for (int p = NSTAT - 1; p < NPAIR; p += 3) pnn_pair(sb, wt, w, lane, p);
    asm volatile("cp.async.wait_all;" ::: "memory");
    asm volatile("barrier.cluster.wait.aligned;" ::: "memory");
  }
}

typedef CUresult (*EncodeFn)(CUtensorMap*, CUtensorMapDataType, cuuint32_t, void*, const cuuint64_t*, const cuuint64_t*, const cuuint32_t*,
                             const cuuint32_t*, CUtensorMapInterleave, CUtensorMapSwizzle, CUtensorMapL2promotion, CUtensorMapFloatOOBfill);
}

extern "C" void kernel_launch(void* const* d_in, const int* in_sizes, int n_in, void* d_out, int out_size) {
  (void)in_sizes; (void)n_in; (void)out_size;
  static EncodeFn enc = nullptr;
  if (!enc) {
    void* fn = nullptr; cudaDriverEntryPointQueryResult qr;
    cudaGetDriverEntryPoint("cuTensorMapEncodeTiled", &fn, cudaEnableDefault, &qr);
    enc = (EncodeFn)fn;
    cudaFuncSetAttribute(pnn_mlp_kernel, cudaFuncAttributeMaxDynamicSharedMemorySize, SMEM_BYTES);
  }
  CUtensorMap tm;
  cuuint64_t dims[5] = {512, 2, 4, 4, 104};
  cuuint64_t strides[4] = {1024, 8 * 1024, 2 * 1024, 32 * 1024};
  cuuint32_t box[5] = {64, 2, 4, 4, 2};
  cuuint32_t es[5] = {1, 1, 1, 1, 1};
  enc(&tm, CU_TENSOR_MAP_DATA_TYPE_BFLOAT16, 5, d_in[3], dims, strides, box, es, CU_TENSOR_MAP_INTERLEAVE_NONE, CU_TENSOR_MAP_SWIZZLE_128B,
      CU_TENSOR_MAP_L2_PROMOTION_L2_128B, CU_TENSOR_MAP_FLOAT_OOB_FILL_NONE);
  cudaLaunchConfig_t cfg = {};
  cfg.gridDim = dim3(128 + NHELP); cfg.blockDim = dim3(512); cfg.dynamicSmemBytes = SMEM_BYTES; cfg.stream = cudaStreamPerThread;
  cudaLaunchAttribute at[1];
  at[0].id = cudaLaunchAttributeClusterDimension; at[0].val.clusterDim.x = 2; at[0].val.clusterDim.y = 1; at[0].val.clusterDim.z = 1;
  cfg.attrs = at; cfg.numAttrs = 1;
  cudaLaunchKernelEx(&cfg, pnn_mlp_kernel, tm, (const int*)d_in[0], (const char*)d_in[1], (const __nv_bfloat16*)d_in[2],
                     (const __nv_bfloat16*)d_in[4], (const __nv_bfloat16*)d_in[5], (const __nv_bfloat16*)d_in[6], (__nv_bfloat16*)d_out, (const void*)d_in[3], 0u);
}
```
